```python
import torch

def _softmax(x, axis=-1):
    return torch.softmax(x, dim=axis)
def _gelu(x):
    return torch.nn.functional.gelu(x, approximate="tanh")
def _silu(x):
    return torch.nn.functional.silu(x)
def _sigmoid(x):
    return torch.sigmoid(x)
def _layernorm(x, axis=-1, eps=1e-5):
    m = x.mean(dim=axis, keepdim=True)
    v = x.var(dim=axis, keepdim=True, unbiased=False)
    return (x - m) / torch.sqrt(v + eps)
def _scatter_add(tgt, idx, src, axis=0):
    return tgt.clone().index_add_(axis, idx, src)
def _segment_sum(src, seg, n):
    out = torch.zeros((n,) + src.shape[1:], dtype=src.dtype)
    return out.index_add_(0, seg, src)
def _pad(x, pw):
    flat = tuple(v for pair in reversed(pw) for v in pair)
    return torch.nn.functional.pad(x, flat)

kernel_name = 'standalone__gqa_softmax__sampling'

def setup_inputs():

    _w = (lambda a: (lambda t: t.to(torch.bfloat16) if t.is_floating_point() else t)(torch.as_tensor(a)))
    B, Hq, Hkv, Sq, Sk, D = 32, 32, 4, 4, 2048, 128
    return {
        "q": _w((lambda *s: torch.randn(*s, dtype=torch.bfloat16) * 0.8)(B, Hq, Sq, D)),
        "k": _w((lambda *s: torch.randn(*s, dtype=torch.bfloat16) * 0.8)(B, Hkv, Sk, D)),
        "v": _w((lambda *s: torch.randn(*s, dtype=torch.bfloat16) * 0.05)(B, Hkv, Sk, D)),
    }

def reference(q, k, v):
    B, Hq, Sq, D = q.shape
    Hkv = k.shape[1]
    rep = Hq // Hkv
    k = (lambda x, n, axis: torch.repeat_interleave(x, n, dim=axis))(k, rep, axis=1)
    v = (lambda x, n, axis: torch.repeat_interleave(x, n, dim=axis))(v, rep, axis=1)
    scale = D ** -0.5
    scores = torch.einsum("bhqd,bhkd->bhqk", q, k) * scale
    p = _softmax(scores, axis=-1)
    return torch.einsum("bhqk,bhkd->bhqd", p, v)
```

```cpp
#include <cuda_runtime.h>
#include <cuda_bf16.h>
#include <cuda.h>
#include <stdint.h>

namespace {

constexpr int kB = 32, kHq = 32, kHkv = 4, kSq = 4, kSk = 2048, kD = 128;
constexpr int kRows = (kHq / kHkv) * kSq;
constexpr int kPairs = kB * kHkv;
constexpr int kTile = 64;
constexpr int kNT = kSk / kTile;
constexpr int kStageBytes = kTile * kD * 2;
#define NSLOTS 5
#define NPASS 1
#define WIN 4
#define ONEPROD 1
#define ST64 1
constexpr int kSlots = NSLOTS;
constexpr int kWin = WIN;
constexpr int kTilesWG = kNT / 2;
constexpr int kLoadsWG = 2 * kTilesWG;
constexpr int kThreads = 384;
constexpr int kRingBytes = kSlots * kStageBytes;
constexpr int kMergeOff = 2 * kRingBytes;
constexpr int kBarOff = kMergeOff + 34 * 128 * 4;
constexpr int kSmemBytes = kBarOff + 4 * kSlots * 8 + 16 + 1024;
static_assert((kBarOff + 4 * kSlots * 8) % 16 == 0, "ticket alignment");

__device__ __forceinline__ uint32_t smem_u32(const void* p) { return (uint32_t)__cvta_generic_to_shared(p); }

__device__ __forceinline__ bool elect_one() {
    uint32_t p;
    asm volatile("{\n .reg .pred q;\n elect.sync _|q, 0xffffffff;\n selp.u32 %0, 1, 0, q;\n}" : "=r"(p));
    return p != 0;
}
__device__ __forceinline__ void mbar_init(uint32_t bar, uint32_t cnt) {
    asm volatile("mbarrier.init.shared::cta.b64 [%0], %1;" ::"r"(bar), "r"(cnt) : "memory");
}
__device__ __forceinline__ void mbar_expect_tx(uint32_t bar, uint32_t bytes) {
    asm volatile("mbarrier.arrive.expect_tx.shared::cta.b64 _, [%0], %1;" ::"r"(bar), "r"(bytes) : "memory");
}
__device__ __forceinline__ void mbar_arrive_pred(uint32_t bar, uint32_t pred) {
    asm volatile("{\n .reg .pred q;\n setp.ne.b32 q, %1, 0;\n @q mbarrier.arrive.shared::cta.b64 _, [%0];\n}"
                 ::"r"(bar), "r"(pred) : "memory");
}
__device__ __forceinline__ void mbar_wait(uint32_t bar, uint32_t parity) {
    asm volatile(
        "{\n"
        " .reg .pred q;\n"
        " .reg .u32 n;\n"
        " mbarrier.try_wait.parity.shared::cta.b64 q, [%0], %1;\n"
        " @q bra DONE;\n"
        " mov.u32 n, 0;\n"
        "SPIN:\n"
        " mbarrier.try_wait.parity.shared::cta.b64 q, [%0], %1;\n"
        " @q bra DONE;\n"
        " add.u32 n, n, 1;\n"
        " setp.lt.u32 q, n, 0x400000;\n"
        " @q bra SPIN;\n"
        " trap;\n"
        "DONE:\n"
        "}" ::"r"(bar), "r"(parity) : "memory");
}
__device__ __forceinline__ void tma_load_tile(uint32_t dst, const CUtensorMap* tm, int row, uint32_t bar) {
    asm volatile(
        "cp.async.bulk.tensor.3d.shared::cluster.global.mbarrier::complete_tx::bytes [%0], [%1, {%3, %4, %5}], [%2];"
        ::"r"(dst), "l"(tm), "r"(bar), "r"(0), "r"(row), "r"(0) : "memory");
}

__device__ __forceinline__ void wg_fence() { asm volatile("wgmma.fence.sync.aligned;" ::: "memory"); }
__device__ __forceinline__ void wg_commit() { asm volatile("wgmma.commit_group.sync.aligned;" ::: "memory"); }
template <int N>
__device__ __forceinline__ void wg_wait() { asm volatile("wgmma.wait_group.sync.aligned %0;" ::"n"(N) : "memory"); }

template <int N>
__device__ __forceinline__ void reg_fence(float (&r)[N]) {
#pragma unroll
    for (int i = 0; i < N; i++) asm volatile("" : "+f"(r[i])::"memory");
}
template <int N>
__device__ __forceinline__ void reg_fence(uint32_t (&r)[N]) {
#pragma unroll
    for (int i = 0; i < N; i++) asm volatile("" : "+r"(r[i])::"memory");
}

#define DESC_HI "0x40000040"

template <int OFF>
__device__ __forceinline__ void wgmma_n64_first(float (&d)[32], const uint32_t* a, uint32_t desc_lo) {
    asm volatile(
        "{\n .reg .pred p;\n .reg .b32 lo;\n .reg .b64 dd;\n setp.ne.b32 p, 0, 0;\n"
        " add.u32 lo, %36, %37;\n mov.b64 dd, {lo, " DESC_HI "};\n"
        "wgmma.mma_async.sync.aligned.m64n64k16.f32.bf16.bf16 "
        "{%0,%1,%2,%3,%4,%5,%6,%7,%8,%9,%10,%11,%12,%13,%14,%15,"
        "%16,%17,%18,%19,%20,%21,%22,%23,%24,%25,%26,%27,%28,%29,%30,%31},"
        "{%32,%33,%34,%35}, dd, p, 1, 1, 0;\n}"
        : "=f"(d[0]), "=f"(d[1]), "=f"(d[2]), "=f"(d[3]), "=f"(d[4]), "=f"(d[5]), "=f"(d[6]), "=f"(d[7]),
          "=f"(d[8]), "=f"(d[9]), "=f"(d[10]), "=f"(d[11]), "=f"(d[12]), "=f"(d[13]), "=f"(d[14]), "=f"(d[15]),
          "=f"(d[16]), "=f"(d[17]), "=f"(d[18]), "=f"(d[19]), "=f"(d[20]), "=f"(d[21]), "=f"(d[22]), "=f"(d[23]),
          "=f"(d[24]), "=f"(d[25]), "=f"(d[26]), "=f"(d[27]), "=f"(d[28]), "=f"(d[29]), "=f"(d[30]), "=f"(d[31])
        : "r"(a[0]), "r"(a[1]), "r"(a[2]), "r"(a[3]), "r"(desc_lo), "n"(OFF));
}
template <int OFF>
__device__ __forceinline__ void wgmma_n64_acc(float (&d)[32], const uint32_t* a, uint32_t desc_lo) {
    asm volatile(
        "{\n .reg .pred p;\n .reg .b32 lo;\n .reg .b64 dd;\n setp.eq.b32 p, 0, 0;\n"
        " add.u32 lo, %36, %37;\n mov.b64 dd, {lo, " DESC_HI "};\n"
        "wgmma.mma_async.sync.aligned.m64n64k16.f32.bf16.bf16 "
        "{%0,%1,%2,%3,%4,%5,%6,%7,%8,%9,%10,%11,%12,%13,%14,%15,"
        "%16,%17,%18,%19,%20,%21,%22,%23,%24,%25,%26,%27,%28,%29,%30,%31},"
        "{%32,%33,%34,%35}, dd, p, 1, 1, 0;\n}"
        : "+f"(d[0]), "+f"(d[1]), "+f"(d[2]), "+f"(d[3]), "+f"(d[4]), "+f"(d[5]), "+f"(d[6]), "+f"(d[7]),
          "+f"(d[8]), "+f"(d[9]), "+f"(d[10]), "+f"(d[11]), "+f"(d[12]), "+f"(d[13]), "+f"(d[14]), "+f"(d[15]),
          "+f"(d[16]), "+f"(d[17]), "+f"(d[18]), "+f"(d[19]), "+f"(d[20]), "+f"(d[21]), "+f"(d[22]), "+f"(d[23]),
          "+f"(d[24]), "+f"(d[25]), "+f"(d[26]), "+f"(d[27]), "+f"(d[28]), "+f"(d[29]), "+f"(d[30]), "+f"(d[31])
        : "r"(a[0]), "r"(a[1]), "r"(a[2]), "r"(a[3]), "r"(desc_lo), "n"(OFF));
}
template <int OFF>
__device__ __forceinline__ void wgmma_n128_t(float (&d)[64], const uint32_t* a, uint32_t desc_lo) {
    asm volatile(
        "{\n .reg .pred p;\n .reg .b32 lo;\n .reg .b64 dd;\n setp.eq.b32 p, 0, 0;\n"
        " add.u32 lo, %68, %69;\n mov.b64 dd, {lo, " DESC_HI "};\n"
        "wgmma.mma_async.sync.aligned.m64n128k16.f32.bf16.bf16 "
        "{%0,%1,%2,%3,%4,%5,%6,%7,%8,%9,%10,%11,%12,%13,%14,%15,"
        "%16,%17,%18,%19,%20,%21,%22,%23,%24,%25,%26,%27,%28,%29,%30,%31,"
        "%32,%33,%34,%35,%36,%37,%38,%39,%40,%41,%42,%43,%44,%45,%46,%47,"
        "%48,%49,%50,%51,%52,%53,%54,%55,%56,%57,%58,%59,%60,%61,%62,%63},"
        "{%64,%65,%66,%67}, dd, p, 1, 1, 1;\n}"
        : "+f"(d[0]), "+f"(d[1]), "+f"(d[2]), "+f"(d[3]), "+f"(d[4]), "+f"(d[5]), "+f"(d[6]), "+f"(d[7]),
          "+f"(d[8]), "+f"(d[9]), "+f"(d[10]), "+f"(d[11]), "+f"(d[12]), "+f"(d[13]), "+f"(d[14]), "+f"(d[15]),
          "+f"(d[16]), "+f"(d[17]), "+f"(d[18]), "+f"(d[19]), "+f"(d[20]), "+f"(d[21]), "+f"(d[22]), "+f"(d[23]),
          "+f"(d[24]), "+f"(d[25]), "+f"(d[26]), "+f"(d[27]), "+f"(d[28]), "+f"(d[29]), "+f"(d[30]), "+f"(d[31]),
          "+f"(d[32]), "+f"(d[33]), "+f"(d[34]), "+f"(d[35]), "+f"(d[36]), "+f"(d[37]), "+f"(d[38]), "+f"(d[39]),
          "+f"(d[40]), "+f"(d[41]), "+f"(d[42]), "+f"(d[43]), "+f"(d[44]), "+f"(d[45]), "+f"(d[46]), "+f"(d[47]),
          "+f"(d[48]), "+f"(d[49]), "+f"(d[50]), "+f"(d[51]), "+f"(d[52]), "+f"(d[53]), "+f"(d[54]), "+f"(d[55]),
          "+f"(d[56]), "+f"(d[57]), "+f"(d[58]), "+f"(d[59]), "+f"(d[60]), "+f"(d[61]), "+f"(d[62]), "+f"(d[63])
        : "r"(a[0]), "r"(a[1]), "r"(a[2]), "r"(a[3]), "r"(desc_lo), "n"(OFF));
}

__device__ __forceinline__ float ex2(float x) {
    float y;
    asm("ex2.approx.ftz.f32 %0, %1;" : "=f"(y) : "f"(x));
    return y;
}
__device__ __forceinline__ uint32_t pack_bf16(float lo, float hi) {
    uint32_t r;
    asm("cvt.rn.bf16x2.f32 %0, %1, %2;" : "=r"(r) : "f"(hi), "f"(lo));
    return r;
}
__device__ __forceinline__ float lds_f32(uint32_t addr) {
    float v;
    asm volatile("ld.shared.f32 %0, [%1];" : "=f"(v) : "r"(addr) : "memory");
    return v;
}
__device__ __forceinline__ void sts_f32(uint32_t addr, float v) {
    asm volatile("st.shared.f32 [%0], %1;" ::"r"(addr), "f"(v) : "memory");
}
__device__ __forceinline__ void st_global_pred(void* p, uint32_t v, uint32_t pred) {
    asm volatile("{\n .reg .pred q;\n setp.ne.b32 q, %2, 0;\n @q st.global.b32 [%0], %1;\n}" ::"l"(p), "r"(v), "r"(pred) : "memory");
}
__device__ __forceinline__ void st_global2_pred(void* p, uint32_t v0, uint32_t v1, uint32_t pred) {
    asm volatile("{\n .reg .pred q;\n setp.ne.b32 q, %3, 0;\n @q st.global.v2.b32 [%0], {%1, %2};\n}"
                 ::"l"(p), "r"(v0), "r"(v1), "r"(pred) : "memory");
}

#define TLW(i, cond) do { } while (0)

__device__ __forceinline__ void issue_load(int i, uint32_t dst, uint32_t bar, const CUtensorMap* tmK,
                                           const CUtensorMap* tmV, int row0) {
    const bool isK = (i == 0) || ((i & 1) && i != kLoadsWG - 1);
    const int j = (i == kLoadsWG - 1) ? kTilesWG - 1 : (isK ? (i + 1) >> 1 : (i - 2) >> 1);
    mbar_expect_tx(bar, kStageBytes);
    tma_load_tile(dst, isK ? tmK : tmV, row0 + j * (2 * kTile), bar);
}

__global__ void __launch_bounds__(kThreads, 1)
gqa_decode_kernel(const __grid_constant__ CUtensorMap tmK, const __grid_constant__ CUtensorMap tmV,
                  const __nv_bfloat16* __restrict__ q, __nv_bfloat16* __restrict__ out, int npass) {
    extern __shared__ uint8_t smem_raw[];
    const int warp = __shfl_sync(0xffffffffu, (int)(threadIdx.x >> 5), 0);
    const int pair = blockIdx.x;
    const uint32_t sbase = (smem_u32(smem_raw) + 1023u) & ~1023u;

    const uint32_t p_ring = sbase + warp * kRingBytes;
    const uint32_t p_full0 = sbase + kBarOff + warp * (kSlots * 8);
    const uint32_t p_empty0 = p_full0 + 2 * kSlots * 8;
    const int p_row0 = pair * kSk + warp * kTile;
    const bool p_active = warp == 0 && elect_one();
    if (p_active) {
#pragma unroll
        for (int s = 0; s < 2 * kSlots; s++) mbar_init(p_full0 + 8 * s, 1);
        asm volatile("fence.mbarrier_init.release.cluster;" ::: "memory");
#pragma unroll
        for (int n = 0; n < kWin; n++)
            issue_load(n >> 1, p_ring + (n & 1) * kRingBytes + (n >> 1) * kStageBytes, p_full0 + (n & 1) * kSlots * 8 + 8 * (n >> 1), &tmK, &tmV, p_row0 + (n & 1) * kTile);
#pragma unroll
        for (int s = 0; s < 2 * kSlots; s++) mbar_init(p_empty0 + 8 * s, 4);
        asm volatile("st.shared.v4.b32 [%0], {%1, %1, %1, %1};" ::"r"(sbase + kBarOff + 4 * kSlots * 8), "r"(0) : "memory");
        asm volatile("fence.mbarrier_init.release.cluster;" ::: "memory");
    }

    if (warp < 4) {
        __syncwarp();
        asm volatile("bar.arrive 0, 384;" ::: "memory");
        asm volatile("setmaxnreg.dec.sync.aligned.u32 40;");
        if (p_active) {
#pragma unroll 1
            for (int n = kWin; n < 2 * kLoadsWG; n++) {
                const int m = n - kWin;
                const int wi = m >> 1, wq = wi / kSlots, wslot = wi - wq * kSlots + (m & 1) * kSlots;
                const int i = n >> 1, iq = i / kSlots, slot = i - iq * kSlots + (n & 1) * kSlots;
                mbar_wait(p_full0 + 8 * wslot, wq & 1);
                mbar_wait(p_empty0 + 8 * slot, (iq & 1) ^ 1);
                issue_load(i, p_ring + slot * kStageBytes, p_full0 + 8 * slot, &tmK, &tmV, p_row0 + (n & 1) * kTile);
            }
        }
    } else {
        const int wg = (warp >> 2) - 1;
        const int w4 = warp & 3;
        const int lane = threadIdx.x & 31;
        const int g = lane >> 2, t = lane & 3;

        const size_t rowoff = ((size_t)pair * kRows + w4 * 8 + g) * kD;
        uint32_t qa[32];
        {
            const uint32_t* qp = reinterpret_cast<const uint32_t*>(q + rowoff) + t;
#pragma unroll
            for (int i = 0; i < 16; i++)
                asm volatile("ld.global.b32 %0, [%1];" : "=r"(qa[2 * i]) : "l"(qp + 4 * i) : "memory");
        }
        asm volatile("bar.sync 0, 384;" ::: "memory");
        asm volatile("setmaxnreg.inc.sync.aligned.u32 232;");

        constexpr float kScaleLog2 = 0.08838834764831845f * 1.4426950408889634f;
        uint32_t full0 = sbase + kBarOff + wg * (kSlots * 8);
        uint32_t ring_lo = ((sbase + wg * kRingBytes) & 0x3FFFF) >> 4;
        uint32_t mbuf = sbase + kMergeOff + (threadIdx.x & 127) * 4;
        uint32_t ticket_addr = sbase + kBarOff + 4 * kSlots * 8 + w4 * 4;
        const uint32_t lane0 = (lane == 0);
        const uint32_t todd = __shfl_sync(0xffffffffu, (uint32_t)(t & 1), lane);
        const uint32_t ooff = __shfl_sync(0xffffffffu, (uint32_t)rowoff * 2 + (t & 1) * 16 + (t >> 1) * 8, lane);

        float o[64];
        float s[32];
        uint32_t p[16];
#pragma unroll
        for (int i = 0; i < 16; i++) asm volatile("" : "=r"(qa[2 * i + 1]));
#pragma unroll
        for (int i = 0; i < 8; i++) asm volatile("" : "=r"(p[2 * i + 1]));

        auto issue_qk = [&](int sl) {
            const uint32_t d = ring_lo + sl * (kStageBytes >> 4) + (1u << 16);
            wgmma_n64_first<0>(s, qa + 0, d);
            wgmma_n64_acc<2>(s, qa + 4, d);
            wgmma_n64_acc<4>(s, qa + 8, d);
            wgmma_n64_acc<6>(s, qa + 12, d);
            wgmma_n64_acc<512>(s, qa + 16, d);
            wgmma_n64_acc<514>(s, qa + 20, d);
            wgmma_n64_acc<516>(s, qa + 24, d);
            wgmma_n64_acc<518>(s, qa + 28, d);
        };
        auto issue_pv = [&](int sl) {
            const uint32_t d = ring_lo + sl * (kStageBytes >> 4) + ((8192u >> 4) << 16);
            wgmma_n128_t<0>(o, p + 0, d);
            wgmma_n128_t<128>(o, p + 4, d);
            wgmma_n128_t<256>(o, p + 8, d);
            wgmma_n128_t<384>(o, p + 12, d);
        };
        float m_run, l_run;
        auto softmax = [&]() -> float {
            const float mx0 = fmaxf(fmaxf(s[0], s[1]), fmaxf(s[4], s[5]));
            const float mx1 = fmaxf(fmaxf(s[8], s[9]), fmaxf(s[12], s[13]));
            const float mx2 = fmaxf(fmaxf(s[16], s[17]), fmaxf(s[20], s[21]));
            const float mx3 = fmaxf(fmaxf(s[24], s[25]), fmaxf(s[28], s[29]));
            float mx = fmaxf(fmaxf(mx0, mx1), fmaxf(fmaxf(mx2, mx3), m_run));
            mx = fmaxf(mx, __shfl_xor_sync(0xffffffffu, mx, 1));
            const float m_new = fmaxf(mx, __shfl_xor_sync(0xffffffffu, mx, 2));
            const float alpha = ex2((m_run - m_new) * kScaleLog2);
            const float mb = m_new * kScaleLog2;
            m_run = m_new;
            float sum0 = 0.f, sum1 = 0.f;
#pragma unroll
            for (int i = 0; i < 8; i++) {
                s[4 * i] = ex2(fmaf(s[4 * i], kScaleLog2, -mb));
                s[4 * i + 1] = ex2(fmaf(s[4 * i + 1], kScaleLog2, -mb));
                sum0 += s[4 * i];
                sum1 += s[4 * i + 1];
            }
            l_run = l_run * alpha + (sum0 + sum1);
            return alpha;
        };
        auto pack_p = [&]() {
#pragma unroll
            for (int i = 0; i < 8; i++) p[2 * i] = pack_bf16(s[4 * i], s[4 * i + 1]);
        };

#pragma unroll 1
        for (int pass = npass; pass > 0; pass--) {
            const uint32_t real = (pass == 1);
#pragma unroll
            for (int i = 0; i < 64; i++) o[i] = 0.f;
#pragma unroll
            for (int i = 0; i < 8; i++) p[2 * i] = 0;
            m_run = -INFINITY;
            l_run = 0.f;
            int slot = 0;
            uint32_t phase = 0;
            if (real) {
                mbar_wait(full0, 0);
                wg_fence();
                issue_qk(0);
                wg_commit();
                wg_wait<0>();
                reg_fence(s);
                mbar_arrive_pred(full0 + 2 * kSlots * 8, lane0);
                slot = 1;
                softmax();
                pack_p();
#pragma unroll 1
                for (int j = 1; j < kTilesWG; j++) {
                    const int slotK = slot;
                    mbar_wait(full0 + 8 * slot, phase);
                    if (++slot == kSlots) { slot = 0; phase ^= 1; }
                    reg_fence(p);
                    wg_fence();
                    issue_qk(slotK);
                    wg_commit();
                    const int slotV = slot;
                    TLW(64 + wg * 32 + j - 1, (threadIdx.x & 127) == 0);
                    mbar_wait(full0 + 8 * slot, phase);
                    TLW(64 + wg * 32 + 16 + j - 1, (threadIdx.x & 127) == 0);
                    if (++slot == kSlots) { slot = 0; phase ^= 1; }
                    reg_fence(o);
                    wg_fence();
                    issue_pv(slotV);
                    wg_commit();
                    wg_wait<1>();
                    reg_fence(s);
                    mbar_arrive_pred(full0 + 2 * kSlots * 8 + 8 * slotK, lane0);
                    const float alpha = softmax();
                    if (__float_as_uint(l_run) == 0xffffffffu) __nanosleep(0);
                    wg_wait<0>();
                    reg_fence(o);
                    reg_fence(p);
                    mbar_arrive_pred(full0 + 2 * kSlots * 8 + 8 * slotV, lane0);
                    pack_p();
#pragma unroll
                    for (int i = 0; i < 16; i++) {
                        o[4 * i] *= alpha;
                        o[4 * i + 1] *= alpha;
                    }
                }
                TLW(64 + wg * 32 + 15, (threadIdx.x & 127) == 0);
                mbar_wait(full0 + 8 * slot, phase);
                TLW(64 + wg * 32 + 31, (threadIdx.x & 127) == 0);
            }
            reg_fence(o);
            reg_fence(p);
            wg_fence();
            issue_pv(slot);
            wg_commit();

            uint32_t ticket = 0;
            asm volatile("{\n .reg .pred q;\n setp.ne.b32 q, %3, 0;\n @q atom.shared.exch.b32 %0, [%1], %2;\n}"
                         : "+r"(ticket) : "r"(ticket_addr), "r"(pass), "r"(lane0) : "memory");
            float l_tot = l_run + __shfl_xor_sync(0xffffffffu, l_run, 1);
            l_tot += __shfl_xor_sync(0xffffffffu, l_tot, 2);
            const bool second = __shfl_sync(0xffffffffu, ticket, 0) == (uint32_t)pass;
            float o0[32];
            float f1 = 0.f;
            if (second) {
                asm volatile("bar.sync %0, 64;" ::"r"(1 + w4) : "memory");
                const float m0 = lds_f32(mbuf + 32 * 512), l0 = lds_f32(mbuf + 33 * 512);
#pragma unroll
                for (int i = 0; i < 32; i++) o0[i] = lds_f32(mbuf + i * 512);
                const float m = fmaxf(m0, m_run);
                const float a0 = ex2((m0 - m) * kScaleLog2), a1 = ex2((m_run - m) * kScaleLog2);
                const float inv = __fdividef(1.0f, l0 * a0 + l_tot * a1);
                const float f0 = a0 * inv;
                f1 = a1 * inv;
#pragma unroll
                for (int i = 0; i < 32; i++) o0[i] *= f0;
            }
            wg_wait<0>();
            reg_fence(o);
            reg_fence(p);
            if (!second) {
#pragma unroll
                for (int i = 0; i < 16; i++) {
                    sts_f32(mbuf + (2 * i) * 512, o[4 * i]);
                    sts_f32(mbuf + (2 * i + 1) * 512, o[4 * i + 1]);
                }
                sts_f32(mbuf + 32 * 512, m_run);
                sts_f32(mbuf + 33 * 512, l_tot);
                asm volatile("bar.arrive %0, 64;" ::"r"(1 + w4) : "memory");
                TLW(42, w4 == 0 && lane0);
            } else {
                char* op = reinterpret_cast<char*>(out) + ooff;
                uint32_t r[16];
#pragma unroll
                for (int i = 0; i < 16; i++)
                    r[i] = pack_bf16(fmaf(o[4 * i], f1, o0[2 * i]), fmaf(o[4 * i + 1], f1, o0[2 * i + 1]));
#pragma unroll
                for (int i = 0; i < 8; i++) {
                    const uint32_t send = todd ? r[2 * i] : r[2 * i + 1];
                    const uint32_t recv = __shfl_xor_sync(0xffffffffu, send, 1);
                    st_global2_pred(op + 32 * i, todd ? recv : r[2 * i], todd ? r[2 * i + 1] : recv, real);
                }
            }
            if (!real) asm volatile("bar.sync 5, 256;" ::: "memory");
        }
    }
}

typedef CUresult (*EncodeFn)(CUtensorMap*, CUtensorMapDataType, cuuint32_t, void*, const cuuint64_t*,
                             const cuuint64_t*, const cuuint32_t*, const cuuint32_t*, CUtensorMapInterleave,
                             CUtensorMapSwizzle, CUtensorMapL2promotion, CUtensorMapFloatOOBfill);

void make_kv_map(EncodeFn enc, CUtensorMap* tm, const void* ptr) {
    cuuint64_t dims[3] = {64, (cuuint64_t)kPairs * kSk, 2};
    cuuint64_t strides[2] = {kD * 2, 128};
    cuuint32_t box[3] = {64, (cuuint32_t)kTile, 2};
    cuuint32_t estr[3] = {1, 1, 1};
    enc(tm, CU_TENSOR_MAP_DATA_TYPE_BFLOAT16, 3, const_cast<void*>(ptr), dims, strides, box, estr,
        CU_TENSOR_MAP_INTERLEAVE_NONE, CU_TENSOR_MAP_SWIZZLE_128B, CU_TENSOR_MAP_L2_PROMOTION_L2_256B,
        CU_TENSOR_MAP_FLOAT_OOB_FILL_NONE);
}

}

extern "C" void kernel_launch(void* const* d_in, const int* in_sizes, int n_in, void* d_out, int out_size) {
    (void)in_sizes; (void)n_in; (void)out_size;
    static EncodeFn enc = nullptr;
    if (!enc) {
        cudaDriverEntryPointQueryResult qr;
        void* fn = nullptr;
        cudaGetDriverEntryPoint("cuTensorMapEncodeTiled", &fn, cudaEnableDefault, &qr);
        enc = (EncodeFn)fn;
        cudaFuncSetAttribute(gqa_decode_kernel, cudaFuncAttributeMaxDynamicSharedMemorySize, kSmemBytes);
    }
    CUtensorMap tmK, tmV;
    make_kv_map(enc, &tmK, d_in[1]);
    make_kv_map(enc, &tmV, d_in[2]);
    gqa_decode_kernel<<<kPairs, kThreads, kSmemBytes, cudaStreamPerThread>>>(
        tmK, tmV, (const __nv_bfloat16*)d_in[0], (__nv_bfloat16*)d_out, NPASS);
}
```

```cpp
#include <cuda_runtime.h>
#include <cuda_bf16.h>
#include <cuda.h>
#include <stdint.h>

namespace {

constexpr int kB = 32, kHq = 32, kHkv = 4, kSq = 4, kSk = 2048, kD = 128;
constexpr int kRows = (kHq / kHkv) * kSq;
constexpr int kPairs = kB * kHkv;
constexpr int kTile = 64;
constexpr int kNT = kSk / kTile;
constexpr int kStageBytes = kTile * kD * 2;
#define NSLOTS 7
#define WIN 8
#define NFIRST 6
#define PACE_NS 650
#define PACE_T63 40200
constexpr int kSlots = NSLOTS;
constexpr int kWin = WIN;
constexpr int kFirst = NFIRST;
constexpr int kTilesWG = kNT / 2;
constexpr int kLoadsWG = 2 * kTilesWG;
constexpr int kThreads = 384;
constexpr int kRingBytes = kSlots * kStageBytes;
constexpr int kMlOff = 2 * kRingBytes;
constexpr int kBarOff = kMlOff + 2 * 128 * 4;
constexpr int kTicketOff = kBarOff + 4 * kSlots * 8;
constexpr int kSmemBytes = kTicketOff + 16 + 1024;
constexpr int kLastKSlot = (kLoadsWG - 3) % kSlots;
static_assert(kTicketOff % 16 == 0, "ticket alignment");
static_assert(kFirst <= kWin && kFirst <= 2 * kSlots && kSlots >= 4, "config");
static_assert(kSmemBytes <= 232448, "shared memory");

__device__ __forceinline__ uint32_t smem_u32(const void* p) { return (uint32_t)__cvta_generic_to_shared(p); }

__device__ __forceinline__ void mbar_init(uint32_t bar, uint32_t cnt) {
    asm volatile("mbarrier.init.shared::cta.b64 [%0], %1;" ::"r"(bar), "r"(cnt) : "memory");
}
__device__ __forceinline__ void mbar_expect_tx(uint32_t bar, uint32_t bytes) {
    asm volatile("mbarrier.arrive.expect_tx.shared::cta.b64 _, [%0], %1;" ::"r"(bar), "r"(bytes) : "memory");
}
__device__ __forceinline__ void mbar_arrive_pred(uint32_t bar, uint32_t pred) {
    asm volatile("{\n .reg .pred q;\n setp.ne.b32 q, %1, 0;\n @q mbarrier.arrive.shared::cta.b64 _, [%0];\n}"
                 ::"r"(bar), "r"(pred) : "memory");
}
__device__ __forceinline__ void mbar_wait(uint32_t bar, uint32_t parity) {
    asm volatile(
        "{\n"
        " .reg .pred q;\n"
        " .reg .u32 n;\n"
        " mbarrier.try_wait.parity.shared::cta.b64 q, [%0], %1;\n"
        " @q bra DONE;\n"
        " mov.u32 n, 0;\n"
        "SPIN:\n"
        " mbarrier.try_wait.parity.shared::cta.b64 q, [%0], %1;\n"
        " @q bra DONE;\n"
        " add.u32 n, n, 1;\n"
        " setp.lt.u32 q, n, 0x400000;\n"
        " @q bra SPIN;\n"
        " trap;\n"
        "DONE:\n"
        "}" ::"r"(bar), "r"(parity) : "memory");
}
__device__ __forceinline__ void tma_load_tile(uint32_t dst, const CUtensorMap* tm, int row, uint32_t bar) {
    asm volatile(
        "cp.async.bulk.tensor.3d.shared::cluster.global.mbarrier::complete_tx::bytes [%0], [%1, {%3, %4, %5}], [%2];"
        ::"r"(dst), "l"(tm), "r"(bar), "r"(0), "r"(row), "r"(0) : "memory");
}
__device__ __forceinline__ uint32_t gtime32() {
    uint32_t t;
    asm volatile("mov.u32 %0, %globaltimer_lo;" : "=r"(t));
    return t;
}

__device__ __forceinline__ void wg_fence() { asm volatile("wgmma.fence.sync.aligned;" ::: "memory"); }
__device__ __forceinline__ void wg_commit() { asm volatile("wgmma.commit_group.sync.aligned;" ::: "memory"); }
template <int N>
__device__ __forceinline__ void wg_wait() { asm volatile("wgmma.wait_group.sync.aligned %0;" ::"n"(N) : "memory"); }

template <int N>
__device__ __forceinline__ void reg_fence(float (&r)[N]) {
#pragma unroll
    for (int i = 0; i < N; i++) asm volatile("" : "+f"(r[i])::"memory");
}
template <int N>
__device__ __forceinline__ void reg_fence(uint32_t (&r)[N]) {
#pragma unroll
    for (int i = 0; i < N; i++) asm volatile("" : "+r"(r[i])::"memory");
}

#define DESC_HI "0x40000040"

template <int OFF>
__device__ __forceinline__ void wgmma_n64_first(float (&d)[32], const uint32_t* a, uint32_t desc_lo) {
    asm volatile(
        "{\n .reg .pred p;\n .reg .b32 lo;\n .reg .b64 dd;\n setp.ne.b32 p, 0, 0;\n"
        " add.u32 lo, %36, %37;\n mov.b64 dd, {lo, " DESC_HI "};\n"
        "wgmma.mma_async.sync.aligned.m64n64k16.f32.bf16.bf16 "
        "{%0,%1,%2,%3,%4,%5,%6,%7,%8,%9,%10,%11,%12,%13,%14,%15,"
        "%16,%17,%18,%19,%20,%21,%22,%23,%24,%25,%26,%27,%28,%29,%30,%31},"
        "{%32,%33,%34,%35}, dd, p, 1, 1, 0;\n}"
        : "=f"(d[0]), "=f"(d[1]), "=f"(d[2]), "=f"(d[3]), "=f"(d[4]), "=f"(d[5]), "=f"(d[6]), "=f"(d[7]),
          "=f"(d[8]), "=f"(d[9]), "=f"(d[10]), "=f"(d[11]), "=f"(d[12]), "=f"(d[13]), "=f"(d[14]), "=f"(d[15]),
          "=f"(d[16]), "=f"(d[17]), "=f"(d[18]), "=f"(d[19]), "=f"(d[20]), "=f"(d[21]), "=f"(d[22]), "=f"(d[23]),
          "=f"(d[24]), "=f"(d[25]), "=f"(d[26]), "=f"(d[27]), "=f"(d[28]), "=f"(d[29]), "=f"(d[30]), "=f"(d[31])
        : "r"(a[0]), "r"(a[1]), "r"(a[2]), "r"(a[3]), "r"(desc_lo), "n"(OFF));
}
template <int OFF>
__device__ __forceinline__ void wgmma_n64_acc(float (&d)[32], const uint32_t* a, uint32_t desc_lo) {
    asm volatile(
        "{\n .reg .pred p;\n .reg .b32 lo;\n .reg .b64 dd;\n setp.eq.b32 p, 0, 0;\n"
        " add.u32 lo, %36, %37;\n mov.b64 dd, {lo, " DESC_HI "};\n"
        "wgmma.mma_async.sync.aligned.m64n64k16.f32.bf16.bf16 "
        "{%0,%1,%2,%3,%4,%5,%6,%7,%8,%9,%10,%11,%12,%13,%14,%15,"
        "%16,%17,%18,%19,%20,%21,%22,%23,%24,%25,%26,%27,%28,%29,%30,%31},"
        "{%32,%33,%34,%35}, dd, p, 1, 1, 0;\n}"
        : "+f"(d[0]), "+f"(d[1]), "+f"(d[2]), "+f"(d[3]), "+f"(d[4]), "+f"(d[5]), "+f"(d[6]), "+f"(d[7]),
          "+f"(d[8]), "+f"(d[9]), "+f"(d[10]), "+f"(d[11]), "+f"(d[12]), "+f"(d[13]), "+f"(d[14]), "+f"(d[15]),
          "+f"(d[16]), "+f"(d[17]), "+f"(d[18]), "+f"(d[19]), "+f"(d[20]), "+f"(d[21]), "+f"(d[22]), "+f"(d[23]),
          "+f"(d[24]), "+f"(d[25]), "+f"(d[26]), "+f"(d[27]), "+f"(d[28]), "+f"(d[29]), "+f"(d[30]), "+f"(d[31])
        : "r"(a[0]), "r"(a[1]), "r"(a[2]), "r"(a[3]), "r"(desc_lo), "n"(OFF));
}
template <int OFF>
__device__ __forceinline__ void wgmma_n128_t(float (&d)[64], const uint32_t* a, uint32_t desc_lo) {
    asm volatile(
        "{\n .reg .pred p;\n .reg .b32 lo;\n .reg .b64 dd;\n setp.eq.b32 p, 0, 0;\n"
        " add.u32 lo, %68, %69;\n mov.b64 dd, {lo, " DESC_HI "};\n"
        "wgmma.mma_async.sync.aligned.m64n128k16.f32.bf16.bf16 "
        "{%0,%1,%2,%3,%4,%5,%6,%7,%8,%9,%10,%11,%12,%13,%14,%15,"
        "%16,%17,%18,%19,%20,%21,%22,%23,%24,%25,%26,%27,%28,%29,%30,%31,"
        "%32,%33,%34,%35,%36,%37,%38,%39,%40,%41,%42,%43,%44,%45,%46,%47,"
        "%48,%49,%50,%51,%52,%53,%54,%55,%56,%57,%58,%59,%60,%61,%62,%63},"
        "{%64,%65,%66,%67}, dd, p, 1, 1, 1;\n}"
        : "+f"(d[0]), "+f"(d[1]), "+f"(d[2]), "+f"(d[3]), "+f"(d[4]), "+f"(d[5]), "+f"(d[6]), "+f"(d[7]),
          "+f"(d[8]), "+f"(d[9]), "+f"(d[10]), "+f"(d[11]), "+f"(d[12]), "+f"(d[13]), "+f"(d[14]), "+f"(d[15]),
          "+f"(d[16]), "+f"(d[17]), "+f"(d[18]), "+f"(d[19]), "+f"(d[20]), "+f"(d[21]), "+f"(d[22]), "+f"(d[23]),
          "+f"(d[24]), "+f"(d[25]), "+f"(d[26]), "+f"(d[27]), "+f"(d[28]), "+f"(d[29]), "+f"(d[30]), "+f"(d[31]),
          "+f"(d[32]), "+f"(d[33]), "+f"(d[34]), "+f"(d[35]), "+f"(d[36]), "+f"(d[37]), "+f"(d[38]), "+f"(d[39]),
          "+f"(d[40]), "+f"(d[41]), "+f"(d[42]), "+f"(d[43]), "+f"(d[44]), "+f"(d[45]), "+f"(d[46]), "+f"(d[47]),
          "+f"(d[48]), "+f"(d[49]), "+f"(d[50]), "+f"(d[51]), "+f"(d[52]), "+f"(d[53]), "+f"(d[54]), "+f"(d[55]),
          "+f"(d[56]), "+f"(d[57]), "+f"(d[58]), "+f"(d[59]), "+f"(d[60]), "+f"(d[61]), "+f"(d[62]), "+f"(d[63])
        : "r"(a[0]), "r"(a[1]), "r"(a[2]), "r"(a[3]), "r"(desc_lo), "n"(OFF));
}

__device__ __forceinline__ float ex2(float x) {
    float y;
    asm("ex2.approx.ftz.f32 %0, %1;" : "=f"(y) : "f"(x));
    return y;
}
__device__ __forceinline__ uint32_t pack_bf16(float lo, float hi) {
    uint32_t r;
    asm("cvt.rn.bf16x2.f32 %0, %1, %2;" : "=r"(r) : "f"(hi), "f"(lo));
    return r;
}
__device__ __forceinline__ float lds_f32(uint32_t addr) {
    float v;
    asm volatile("ld.shared.f32 %0, [%1];" : "=f"(v) : "r"(addr) : "memory");
    return v;
}
__device__ __forceinline__ void sts_f32(uint32_t addr, float v) {
    asm volatile("st.shared.f32 [%0], %1;" ::"r"(addr), "f"(v) : "memory");
}

#define TLW(i, cond) do { } while (0)

__device__ __forceinline__ void issue_load(int n, uint32_t dst, uint32_t bar, const CUtensorMap* tmK,
                                           const CUtensorMap* tmV, int row0) {
    const int tile = ((n >> 3) << 2) | (n & 3);
    mbar_expect_tx(bar, kStageBytes);
    tma_load_tile(dst, (n & 4) ? tmV : tmK, row0 + tile * kTile, bar);
}

__global__ void __launch_bounds__(kThreads, 1)
gqa_decode_kernel(const __grid_constant__ CUtensorMap tmK, const __grid_constant__ CUtensorMap tmV,
                  const __nv_bfloat16* __restrict__ q, __nv_bfloat16* __restrict__ out
                  ) {
    constexpr int pace_ns = PACE_NS, pace_off = PACE_T63 - 63 * PACE_NS;
    extern __shared__ uint8_t smem_raw[];
    const int pair = blockIdx.x;
    const uint32_t sbase = (smem_u32(smem_raw) + 1023u) & ~1023u;
    const uint32_t bars = sbase + kBarOff;
    const int row0 = pair * kSk;

    const bool p_active = threadIdx.x == 0;
    uint32_t t_start = 0;
    if (p_active) {
#pragma unroll
        for (int n = 0; n < kFirst; n++) mbar_init(bars + 8 * ((n & 1) * kSlots + (n >> 1)), 1);
        asm volatile("fence.mbarrier_init.release.cluster;" ::: "memory");
        issue_load(0, sbase, bars, &tmK, &tmV, row0);
        t_start = gtime32();
#pragma unroll
        for (int n = 1; n < kFirst; n++) {
            const int slot = (n & 1) * kSlots + (n >> 1);
            issue_load(n, sbase + slot * kStageBytes, bars + 8 * slot, &tmK, &tmV, row0);
        }
#pragma unroll
        for (int n = kFirst; n < 2 * kSlots; n++) mbar_init(bars + 8 * ((n & 1) * kSlots + (n >> 1)), 1);
#pragma unroll
        for (int s = 0; s < 2 * kSlots; s++) mbar_init(bars + 2 * kSlots * 8 + 8 * s, 4);
        asm volatile("st.shared.v4.b32 [%0], {%1, %1, %1, %1};" ::"r"(sbase + kTicketOff), "r"(0) : "memory");
        asm volatile("fence.mbarrier_init.release.cluster;" ::: "memory");
    }

    const int warp = __shfl_sync(0xffffffffu, (int)(threadIdx.x >> 5), 0);
    if (warp < 4) {
        __syncwarp();
        asm volatile("bar.arrive 0, 384;" ::: "memory");
        asm volatile("setmaxnreg.dec.sync.aligned.u32 40;");
        if (p_active) {
#pragma unroll 1
            for (int n = kFirst; n < 2 * kLoadsWG; n++) {
                const int m = n - kWin;
                if (m >= 0) {
                    const int wi = m >> 1, wq = wi / kSlots;
                    mbar_wait(bars + 8 * (wi - wq * kSlots + (m & 1) * kSlots), wq & 1);
                }
                const int i = n >> 1, iq = i / kSlots, slot = i - iq * kSlots + (n & 1) * kSlots;
                mbar_wait(bars + 2 * kSlots * 8 + 8 * slot, (iq & 1) ^ 1);
                const uint32_t due = t_start + (uint32_t)(pace_off + n * pace_ns);
                for (int it = 0; it < 4096 && (int)(gtime32() - due) < 0; it++) { }
                issue_load(n, sbase + slot * kStageBytes, bars + 8 * slot, &tmK, &tmV, row0);
            }
        }
    } else {
        const int wg = (warp >> 2) - 1;
        const int w4 = warp & 3;
        const int lane = threadIdx.x & 31;
        const int g = lane >> 2, t = lane & 3;

        const size_t rowoff = ((size_t)pair * kRows + w4 * 8 + g) * kD;
        uint32_t qa[32];
        {
            const uint32_t* qp = reinterpret_cast<const uint32_t*>(q + rowoff) + t;
#pragma unroll
            for (int i = 0; i < 16; i++)
                asm volatile("ld.global.b32 %0, [%1];" : "=r"(qa[2 * i]) : "l"(qp + 4 * i) : "memory");
        }
        asm volatile("bar.sync 0, 384;" ::: "memory");
        asm volatile("setmaxnreg.inc.sync.aligned.u32 232;");

        constexpr float kScaleLog2 = 0.08838834764831845f * 1.4426950408889634f;
        const uint32_t full0 = bars + wg * (kSlots * 8);
        const uint32_t empty0 = full0 + 2 * kSlots * 8;
        const uint32_t ring_lo = ((sbase + wg * kRingBytes) & 0x3FFFF) >> 4;
        const uint32_t lane0 = (lane == 0);
        const uint32_t todd = __shfl_sync(0xffffffffu, (uint32_t)(t & 1), lane);
        const uint32_t ooff = __shfl_sync(0xffffffffu, (uint32_t)rowoff * 2 + (t & 1) * 16 + (t >> 1) * 8, lane);
        const uint32_t toff = __shfl_sync(0xffffffffu, (threadIdx.x & 127) * 4, lane);

        float o[64];
        float s[32];
        uint32_t p[16];
#pragma unroll
        for (int i = 0; i < 16; i++) asm volatile("" : "=r"(qa[2 * i + 1]));
#pragma unroll
        for (int i = 0; i < 8; i++) asm volatile("" : "=r"(p[2 * i + 1]));
#pragma unroll
        for (int i = 0; i < 64; i++) o[i] = 0.f;
        float m_run = -INFINITY, l_run = 0.f;

        auto issue_qk = [&](int sl) {
            const uint32_t d = ring_lo + sl * (kStageBytes >> 4) + (1u << 16);
            wgmma_n64_first<0>(s, qa + 0, d);
            wgmma_n64_acc<2>(s, qa + 4, d);
            wgmma_n64_acc<4>(s, qa + 8, d);
            wgmma_n64_acc<6>(s, qa + 12, d);
            wgmma_n64_acc<512>(s, qa + 16, d);
            wgmma_n64_acc<514>(s, qa + 20, d);
            wgmma_n64_acc<516>(s, qa + 24, d);
            wgmma_n64_acc<518>(s, qa + 28, d);
        };
        auto issue_pv = [&](int sl) {
            const uint32_t d = ring_lo + sl * (kStageBytes >> 4) + ((8192u >> 4) << 16);
            wgmma_n128_t<0>(o, p + 0, d);
            wgmma_n128_t<128>(o, p + 4, d);
            wgmma_n128_t<256>(o, p + 8, d);
            wgmma_n128_t<384>(o, p + 12, d);
        };
        auto softmax = [&]() -> float {
            const float mx0 = fmaxf(fmaxf(s[0], s[1]), fmaxf(s[4], s[5]));
            const float mx1 = fmaxf(fmaxf(s[8], s[9]), fmaxf(s[12], s[13]));
            const float mx2 = fmaxf(fmaxf(s[16], s[17]), fmaxf(s[20], s[21]));
            const float mx3 = fmaxf(fmaxf(s[24], s[25]), fmaxf(s[28], s[29]));
            float mx = fmaxf(fmaxf(mx0, mx1), fmaxf(fmaxf(mx2, mx3), m_run));
            mx = fmaxf(mx, __shfl_xor_sync(0xffffffffu, mx, 1));
            const float m_new = fmaxf(mx, __shfl_xor_sync(0xffffffffu, mx, 2));
            const float alpha = ex2((m_run - m_new) * kScaleLog2);
            const float mb = m_new * kScaleLog2;
            m_run = m_new;
            float sum0 = 0.f, sum1 = 0.f;
#pragma unroll
            for (int i = 0; i < 8; i++) {
                s[4 * i] = ex2(fmaf(s[4 * i], kScaleLog2, -mb));
                s[4 * i + 1] = ex2(fmaf(s[4 * i + 1], kScaleLog2, -mb));
                sum0 += s[4 * i];
                sum1 += s[4 * i + 1];
            }
            l_run = l_run * alpha + (sum0 + sum1);
            return alpha;
        };
        auto pack_p = [&]() {
#pragma unroll
            for (int i = 0; i < 8; i++) p[2 * i] = pack_bf16(s[4 * i], s[4 * i + 1]);
        };
        auto rescale = [&](float alpha) {
#pragma unroll
            for (int i = 0; i < 16; i++) {
                asm volatile("mul.f32 %0, %0, %1;" : "+f"(o[4 * i]) : "f"(alpha));
                asm volatile("mul.f32 %0, %0, %1;" : "+f"(o[4 * i + 1]) : "f"(alpha));
            }
        };

        int slot = 0;
        uint32_t phase = 0;
        auto advance = [&]() {
            if (++slot == kSlots) { slot = 0; phase ^= 1; }
        };
        auto do_qk = [&]() -> float {
            reg_fence(p);
            mbar_wait(full0 + 8 * slot, phase);
            wg_fence();
            issue_qk(slot);
            wg_commit();
            wg_wait<0>();
            reg_fence(s);
            mbar_arrive_pred(empty0 + 8 * slot, lane0);
            advance();
            return softmax();
        };
        auto do_pv = [&]() {
            reg_fence(o);
            reg_fence(p);
            wg_fence();
            issue_pv(slot);
            wg_commit();
            wg_wait<0>();
            reg_fence(o);
            reg_fence(p);
            mbar_arrive_pred(empty0 + 8 * slot, lane0);
            advance();
        };
#pragma unroll
        for (int i = 0; i < 8; i++) p[2 * i] = 0;
        do_qk();
        pack_p();
        float alpha_b = do_qk();
#pragma unroll 1
        for (int grp = 0;; grp++) {
            TLW(64 + wg * 32 + 2 * grp, (threadIdx.x & 127) == 0);
            mbar_wait(full0 + 8 * slot, phase);
            TLW(64 + wg * 32 + 16 + 2 * grp, (threadIdx.x & 127) == 0);
            do_pv();
            pack_p();
            rescale(alpha_b);
            if (grp == kTilesWG / 2 - 1) asm volatile("bar.sync %0, 128;" ::"r"(5 + wg) : "memory");
            TLW(64 + wg * 32 + 2 * grp + 1, (threadIdx.x & 127) == 0);
            mbar_wait(full0 + 8 * slot, phase);
            TLW(64 + wg * 32 + 16 + 2 * grp + 1, (threadIdx.x & 127) == 0);
            if (grp == kTilesWG / 2 - 1) break;
            do_pv();
            rescale(do_qk());
            pack_p();
            alpha_b = do_qk();
        }
        reg_fence(o);
        reg_fence(p);
        wg_fence();
        issue_pv(slot);
        wg_commit();

        uint32_t ticket = 0;
        asm volatile("{\n .reg .pred q;\n setp.ne.b32 q, %2, 0;\n @q atom.shared.exch.b32 %0, [%1], 1;\n}"
                     : "+r"(ticket) : "r"(sbase + kTicketOff + w4 * 4), "r"(lane0) : "memory");
        float l_tot = l_run + __shfl_xor_sync(0xffffffffu, l_run, 1);
        l_tot += __shfl_xor_sync(0xffffffffu, l_tot, 2);
        const bool second = __shfl_sync(0xffffffffu, ticket, 0) != 0;
        const uint32_t mlbuf = sbase + kMlOff + toff;
        float o0[32];
        float f1 = 0.f;
        if (second) {
            const uint32_t obuf = sbase + (wg ^ 1) * kRingBytes + kLastKSlot * kStageBytes + toff;
            asm volatile("bar.sync %0, 64;" ::"r"(1 + w4) : "memory");
            const float m0 = lds_f32(mlbuf), l0 = lds_f32(mlbuf + 512);
#pragma unroll
            for (int i = 0; i < 32; i++) o0[i] = lds_f32(obuf + i * 512);
            const float m = fmaxf(m0, m_run);
            const float a0 = ex2((m0 - m) * kScaleLog2), a1 = ex2((m_run - m) * kScaleLog2);
            const float inv = __fdividef(1.0f, l0 * a0 + l_tot * a1);
            const float f0 = a0 * inv;
            f1 = a1 * inv;
#pragma unroll
            for (int i = 0; i < 32; i++) o0[i] *= f0;
        }
        wg_wait<0>();
        reg_fence(o);
        reg_fence(p);
        if (!second) {
            const uint32_t obuf = sbase + wg * kRingBytes + kLastKSlot * kStageBytes + toff;
#pragma unroll
            for (int i = 0; i < 16; i++) {
                sts_f32(obuf + (2 * i) * 512, o[4 * i]);
                sts_f32(obuf + (2 * i + 1) * 512, o[4 * i + 1]);
            }
            sts_f32(mlbuf, m_run);
            sts_f32(mlbuf + 512, l_tot);
            asm volatile("bar.arrive %0, 64;" ::"r"(1 + w4) : "memory");
            TLW(42, w4 == 0 && lane0);
        } else {
            char* op = reinterpret_cast<char*>(out) + ooff;
            uint32_t r[16];
#pragma unroll
            for (int i = 0; i < 16; i++)
                r[i] = pack_bf16(fmaf(o[4 * i], f1, o0[2 * i]), fmaf(o[4 * i + 1], f1, o0[2 * i + 1]));
#pragma unroll
            for (int i = 0; i < 8; i++) {
                const uint32_t send = todd ? r[2 * i] : r[2 * i + 1];
                const uint32_t recv = __shfl_xor_sync(0xffffffffu, send, 1);
                *reinterpret_cast<uint2*>(op + 32 * i) = make_uint2(todd ? recv : r[2 * i], todd ? r[2 * i + 1] : recv);
            }
        }
    }
}

typedef CUresult (*EncodeFn)(CUtensorMap*, CUtensorMapDataType, cuuint32_t, void*, const cuuint64_t*,
                             const cuuint64_t*, const cuuint32_t*, const cuuint32_t*, CUtensorMapInterleave,
                             CUtensorMapSwizzle, CUtensorMapL2promotion, CUtensorMapFloatOOBfill);

void make_kv_map(EncodeFn enc, CUtensorMap* tm, const void* ptr) {
    cuuint64_t dims[3] = {64, (cuuint64_t)kPairs * kSk, 2};
    cuuint64_t strides[2] = {kD * 2, 128};
    cuuint32_t box[3] = {64, (cuuint32_t)kTile, 2};
    cuuint32_t estr[3] = {1, 1, 1};
    enc(tm, CU_TENSOR_MAP_DATA_TYPE_BFLOAT16, 3, const_cast<void*>(ptr), dims, strides, box, estr,
        CU_TENSOR_MAP_INTERLEAVE_NONE, CU_TENSOR_MAP_SWIZZLE_128B, CU_TENSOR_MAP_L2_PROMOTION_L2_256B,
        CU_TENSOR_MAP_FLOAT_OOB_FILL_NONE);
}

}

extern "C" void kernel_launch(void* const* d_in, const int* in_sizes, int n_in, void* d_out, int out_size) {
    (void)in_sizes; (void)n_in; (void)out_size;
    static EncodeFn enc = nullptr;
    if (!enc) {
        cudaDriverEntryPointQueryResult qr;
        void* fn = nullptr;
        cudaGetDriverEntryPoint("cuTensorMapEncodeTiled", &fn, cudaEnableDefault, &qr);
        enc = (EncodeFn)fn;
        cudaFuncSetAttribute(gqa_decode_kernel, cudaFuncAttributeMaxDynamicSharedMemorySize, kSmemBytes);
    }
    CUtensorMap tmK, tmV;
    make_kv_map(enc, &tmK, d_in[1]);
    make_kv_map(enc, &tmV, d_in[2]);
    gqa_decode_kernel<<<kPairs, kThreads, kSmemBytes, cudaStreamPerThread>>>(
        tmK, tmV, (const __nv_bfloat16*)d_in[0], (__nv_bfloat16*)d_out
        );
}
```

```cpp
#include <cuda_runtime.h>
#include <cuda_bf16.h>
#include <cuda.h>
#include <stdint.h>

namespace {

constexpr int kB = 32, kHq = 32, kHkv = 4, kSq = 4, kSk = 2048, kD = 128;
constexpr int kRows = (kHq / kHkv) * kSq;
constexpr int kPairs = kB * kHkv;
constexpr int kTile = 64;
constexpr int kNT = kSk / kTile;
constexpr int kStageBytes = kTile * kD * 2;
constexpr int kSlots = 7;
constexpr int kWin = 8;
constexpr int kFirst = 4;
constexpr int kPaceNs = 650;
constexpr int kPaceOffNs = 40150 - 63 * kPaceNs;
constexpr int kBurstLo = 4, kBurstHi = 60;
constexpr int kTilesWG = kNT / 2;
constexpr int kLoadsWG = 2 * kTilesWG;
constexpr int kThreads = 384;
constexpr int kRingBytes = kSlots * kStageBytes;
constexpr int kMlOff = 2 * kRingBytes;
constexpr int kBarOff = kMlOff + 2 * 32 * 8;
constexpr int kHandOff = kBarOff + 4 * kSlots * 8;
constexpr int kSmemBytes = kHandOff + 32 + 1024;
constexpr int kLastKSlot = (kLoadsWG - 3) % kSlots;
static_assert(kFirst == 4, "barrier init split");
static_assert(kFirst <= kWin && kFirst <= 2 * kSlots && kSlots >= 4, "config");
static_assert(kSmemBytes <= 232448, "shared memory");

__device__ __forceinline__ uint32_t smem_u32(const void* p) { return (uint32_t)__cvta_generic_to_shared(p); }

__device__ __forceinline__ void mbar_init(uint32_t bar, uint32_t cnt) {
    asm volatile("mbarrier.init.shared::cta.b64 [%0], %1;" ::"r"(bar), "r"(cnt) : "memory");
}
__device__ __forceinline__ void mbar_expect_tx(uint32_t bar, uint32_t bytes) {
    asm volatile("mbarrier.arrive.expect_tx.shared::cta.b64 _, [%0], %1;" ::"r"(bar), "r"(bytes) : "memory");
}
__device__ __forceinline__ void mbar_arrive_pred(uint32_t bar, uint32_t pred) {
    asm volatile("{\n .reg .pred q;\n setp.ne.b32 q, %1, 0;\n @q mbarrier.arrive.shared::cta.b64 _, [%0];\n}"
                 ::"r"(bar), "r"(pred) : "memory");
}
__device__ __forceinline__ void mbar_wait(uint32_t bar, uint32_t parity) {
    asm volatile(
        "{\n"
        " .reg .pred q;\n"
        " .reg .u32 n;\n"
        " mbarrier.try_wait.parity.shared::cta.b64 q, [%0], %1;\n"
        " @q bra DONE;\n"
        " mov.u32 n, 0;\n"
        "SPIN:\n"
        " mbarrier.try_wait.parity.shared::cta.b64 q, [%0], %1;\n"
        " @q bra DONE;\n"
        " add.u32 n, n, 1;\n"
        " setp.lt.u32 q, n, 0x400000;\n"
        " @q bra SPIN;\n"
        " trap;\n"
        "DONE:\n"
        "}" ::"r"(bar), "r"(parity) : "memory");
}
__device__ __forceinline__ void tma_load_tile(uint32_t dst, const CUtensorMap* tm, int row, uint32_t bar) {
    asm volatile(
        "cp.async.bulk.tensor.3d.shared::cluster.global.mbarrier::complete_tx::bytes [%0], [%1, {%3, %4, %5}], [%2];"
        ::"r"(dst), "l"(tm), "r"(bar), "r"(0), "r"(row), "r"(0) : "memory");
}
__device__ __forceinline__ uint32_t gtime32() {
    uint32_t t;
    asm volatile("mov.u32 %0, %globaltimer_lo;" : "=r"(t));
    return t;
}

__device__ __forceinline__ void wg_fence() { asm volatile("wgmma.fence.sync.aligned;" ::: "memory"); }
__device__ __forceinline__ void wg_commit() { asm volatile("wgmma.commit_group.sync.aligned;" ::: "memory"); }
template <int N>
__device__ __forceinline__ void wg_wait() { asm volatile("wgmma.wait_group.sync.aligned %0;" ::"n"(N) : "memory"); }

template <int N>
__device__ __forceinline__ void reg_fence(float (&r)[N]) {
#pragma unroll
    for (int i = 0; i < N; i++) asm volatile("" : "+f"(r[i])::"memory");
}
template <int N>
__device__ __forceinline__ void reg_fence(uint32_t (&r)[N]) {
#pragma unroll
    for (int i = 0; i < N; i++) asm volatile("" : "+r"(r[i])::"memory");
}

#define DESC_HI "0x40000040"

template <int OFF>
__device__ __forceinline__ void wgmma_n64_first(float (&d)[32], const uint32_t* a, uint32_t desc_lo) {
    asm volatile(
        "{\n .reg .pred p;\n .reg .b32 lo;\n .reg .b64 dd;\n setp.ne.b32 p, 0, 0;\n"
        " add.u32 lo, %36, %37;\n mov.b64 dd, {lo, " DESC_HI "};\n"
        "wgmma.mma_async.sync.aligned.m64n64k16.f32.bf16.bf16 "
        "{%0,%1,%2,%3,%4,%5,%6,%7,%8,%9,%10,%11,%12,%13,%14,%15,"
        "%16,%17,%18,%19,%20,%21,%22,%23,%24,%25,%26,%27,%28,%29,%30,%31},"
        "{%32,%33,%34,%35}, dd, p, 1, 1, 0;\n}"
        : "=f"(d[0]), "=f"(d[1]), "=f"(d[2]), "=f"(d[3]), "=f"(d[4]), "=f"(d[5]), "=f"(d[6]), "=f"(d[7]),
          "=f"(d[8]), "=f"(d[9]), "=f"(d[10]), "=f"(d[11]), "=f"(d[12]), "=f"(d[13]), "=f"(d[14]), "=f"(d[15]),
          "=f"(d[16]), "=f"(d[17]), "=f"(d[18]), "=f"(d[19]), "=f"(d[20]), "=f"(d[21]), "=f"(d[22]), "=f"(d[23]),
          "=f"(d[24]), "=f"(d[25]), "=f"(d[26]), "=f"(d[27]), "=f"(d[28]), "=f"(d[29]), "=f"(d[30]), "=f"(d[31])
        : "r"(a[0]), "r"(a[1]), "r"(a[2]), "r"(a[3]), "r"(desc_lo), "n"(OFF));
}
template <int OFF>
__device__ __forceinline__ void wgmma_n64_acc(float (&d)[32], const uint32_t* a, uint32_t desc_lo) {
    asm volatile(
        "{\n .reg .pred p;\n .reg .b32 lo;\n .reg .b64 dd;\n setp.eq.b32 p, 0, 0;\n"
        " add.u32 lo, %36, %37;\n mov.b64 dd, {lo, " DESC_HI "};\n"
        "wgmma.mma_async.sync.aligned.m64n64k16.f32.bf16.bf16 "
        "{%0,%1,%2,%3,%4,%5,%6,%7,%8,%9,%10,%11,%12,%13,%14,%15,"
        "%16,%17,%18,%19,%20,%21,%22,%23,%24,%25,%26,%27,%28,%29,%30,%31},"
        "{%32,%33,%34,%35}, dd, p, 1, 1, 0;\n}"
        : "+f"(d[0]), "+f"(d[1]), "+f"(d[2]), "+f"(d[3]), "+f"(d[4]), "+f"(d[5]), "+f"(d[6]), "+f"(d[7]),
          "+f"(d[8]), "+f"(d[9]), "+f"(d[10]), "+f"(d[11]), "+f"(d[12]), "+f"(d[13]), "+f"(d[14]), "+f"(d[15]),
          "+f"(d[16]), "+f"(d[17]), "+f"(d[18]), "+f"(d[19]), "+f"(d[20]), "+f"(d[21]), "+f"(d[22]), "+f"(d[23]),
          "+f"(d[24]), "+f"(d[25]), "+f"(d[26]), "+f"(d[27]), "+f"(d[28]), "+f"(d[29]), "+f"(d[30]), "+f"(d[31])
        : "r"(a[0]), "r"(a[1]), "r"(a[2]), "r"(a[3]), "r"(desc_lo), "n"(OFF));
}
template <int OFF>
__device__ __forceinline__ void wgmma_n128_t(float (&d)[64], const uint32_t* a, uint32_t desc_lo) {
    asm volatile(
        "{\n .reg .pred p;\n .reg .b32 lo;\n .reg .b64 dd;\n setp.eq.b32 p, 0, 0;\n"
        " add.u32 lo, %68, %69;\n mov.b64 dd, {lo, " DESC_HI "};\n"
        "wgmma.mma_async.sync.aligned.m64n128k16.f32.bf16.bf16 "
        "{%0,%1,%2,%3,%4,%5,%6,%7,%8,%9,%10,%11,%12,%13,%14,%15,"
        "%16,%17,%18,%19,%20,%21,%22,%23,%24,%25,%26,%27,%28,%29,%30,%31,"
        "%32,%33,%34,%35,%36,%37,%38,%39,%40,%41,%42,%43,%44,%45,%46,%47,"
        "%48,%49,%50,%51,%52,%53,%54,%55,%56,%57,%58,%59,%60,%61,%62,%63},"
        "{%64,%65,%66,%67}, dd, p, 1, 1, 1;\n}"
        : "+f"(d[0]), "+f"(d[1]), "+f"(d[2]), "+f"(d[3]), "+f"(d[4]), "+f"(d[5]), "+f"(d[6]), "+f"(d[7]),
          "+f"(d[8]), "+f"(d[9]), "+f"(d[10]), "+f"(d[11]), "+f"(d[12]), "+f"(d[13]), "+f"(d[14]), "+f"(d[15]),
          "+f"(d[16]), "+f"(d[17]), "+f"(d[18]), "+f"(d[19]), "+f"(d[20]), "+f"(d[21]), "+f"(d[22]), "+f"(d[23]),
          "+f"(d[24]), "+f"(d[25]), "+f"(d[26]), "+f"(d[27]), "+f"(d[28]), "+f"(d[29]), "+f"(d[30]), "+f"(d[31]),
          "+f"(d[32]), "+f"(d[33]), "+f"(d[34]), "+f"(d[35]), "+f"(d[36]), "+f"(d[37]), "+f"(d[38]), "+f"(d[39]),
          "+f"(d[40]), "+f"(d[41]), "+f"(d[42]), "+f"(d[43]), "+f"(d[44]), "+f"(d[45]), "+f"(d[46]), "+f"(d[47]),
          "+f"(d[48]), "+f"(d[49]), "+f"(d[50]), "+f"(d[51]), "+f"(d[52]), "+f"(d[53]), "+f"(d[54]), "+f"(d[55]),
          "+f"(d[56]), "+f"(d[57]), "+f"(d[58]), "+f"(d[59]), "+f"(d[60]), "+f"(d[61]), "+f"(d[62]), "+f"(d[63])
        : "r"(a[0]), "r"(a[1]), "r"(a[2]), "r"(a[3]), "r"(desc_lo), "n"(OFF));
}

__device__ __forceinline__ float ex2(float x) {
    float y;
    asm("ex2.approx.ftz.f32 %0, %1;" : "=f"(y) : "f"(x));
    return y;
}
__device__ __forceinline__ uint32_t pack_bf16(float lo, float hi) {
    uint32_t r;
    asm("cvt.rn.bf16x2.f32 %0, %1, %2;" : "=r"(r) : "f"(hi), "f"(lo));
    return r;
}
__device__ __forceinline__ void lds_f32x4(uint32_t addr, float& a, float& b, float& c, float& d) {
    asm volatile("ld.shared.v4.f32 {%0, %1, %2, %3}, [%4];" : "=f"(a), "=f"(b), "=f"(c), "=f"(d) : "r"(addr) : "memory");
}
__device__ __forceinline__ void sts_f32x4(uint32_t addr, float a, float b, float c, float d) {
    asm volatile("st.shared.v4.f32 [%0], {%1, %2, %3, %4};" ::"r"(addr), "f"(a), "f"(b), "f"(c), "f"(d) : "memory");
}

__host__ __device__ constexpr int ring_of(int n) { return (n >> 1) & 1; }
__host__ __device__ constexpr int local_of(int n) { return ((n >> 2) << 1) | (n & 1); }
__device__ __forceinline__ void issue_load(int n, uint32_t dst, uint32_t bar, const CUtensorMap* tmK,
                                           const CUtensorMap* tmV, int row0) {
    const int tile = ((n >> 3) << 2) | (n & 3);
    mbar_expect_tx(bar, kStageBytes);
    tma_load_tile(dst, (n & 4) ? tmV : tmK, row0 + tile * kTile, bar);
}

__global__ void __launch_bounds__(kThreads, 1)
gqa_decode_kernel(const __grid_constant__ CUtensorMap tmK, const __grid_constant__ CUtensorMap tmV,
                  const __nv_bfloat16* __restrict__ q, __nv_bfloat16* __restrict__ out) {
    extern __shared__ uint8_t smem_raw[];
    const int pair = (((blockIdx.x + (blockIdx.x >> 3)) & 7) << 4) | (blockIdx.x >> 3);
    const uint32_t sbase = (smem_u32(smem_raw) + 1023u) & ~1023u;
    const uint32_t bars = sbase + kBarOff;
    const int row0 = pair * kSk;

    const bool p_active = threadIdx.x == 0;
    uint32_t t_start = 0;
    if (p_active) {
#pragma unroll
        for (int n = 0; n < kFirst; n++) mbar_init(bars + 8 * (ring_of(n) * kSlots + local_of(n)), 1);
        asm volatile("fence.mbarrier_init.release.cluster;" ::: "memory");
        issue_load(0, sbase, bars, &tmK, &tmV, row0);
        t_start = gtime32();
#pragma unroll
        for (int n = 1; n < kFirst; n++) {
            const int slot = ring_of(n) * kSlots + local_of(n);
            issue_load(n, sbase + slot * kStageBytes, bars + 8 * slot, &tmK, &tmV, row0);
        }
#pragma unroll
        for (int s = 0; s < 2 * kSlots; s++)
            if (s % kSlots >= 2) mbar_init(bars + 8 * s, 1);
#pragma unroll
        for (int s = 0; s < 2 * kSlots; s++) mbar_init(bars + 2 * kSlots * 8 + 8 * s, 4);
#pragma unroll
        for (int s = 0; s < 4; s++) mbar_init(sbase + kHandOff + 8 * s, 2);
        asm volatile("fence.mbarrier_init.release.cluster;" ::: "memory");
    }

    const int warp = __shfl_sync(0xffffffffu, (int)(threadIdx.x >> 5), 0);
    if (warp < 4) {
        __syncwarp();
        asm volatile("bar.arrive 0, 384;" ::: "memory");
        asm volatile("setmaxnreg.dec.sync.aligned.u32 40;");
        if (p_active) {
#pragma unroll 1
            for (int n = kFirst; n < 2 * kLoadsWG; n++) {
                const int m = n - kWin;
                if (m >= 0) {
                    const int wi = local_of(m), wq = wi / kSlots;
                    mbar_wait(bars + 8 * (wi - wq * kSlots + ring_of(m) * kSlots), wq & 1);
                }
                const int i = local_of(n), iq = i / kSlots, slot = i - iq * kSlots + ring_of(n) * kSlots;
                mbar_wait(bars + 2 * kSlots * 8 + 8 * slot, (iq & 1) ^ 1);
                const int turn = (n >= kBurstLo && n < kBurstHi) ? (n & ~3) + (pair >> 5) : n;
                const uint32_t due = t_start + (uint32_t)(kPaceOffNs + turn * kPaceNs);
                for (int it = 0; it < 4096 && (int)(gtime32() - due) < 0; it++) { }
                issue_load(n, sbase + slot * kStageBytes, bars + 8 * slot, &tmK, &tmV, row0);
            }
        }
    } else {
        const int wg = (warp >> 2) - 1;
        const int w4 = warp & 3;
        const int lane = threadIdx.x & 31;
        const int g = lane >> 2, t = lane & 3;

        const size_t rowoff = ((size_t)pair * kRows + w4 * 8 + g) * kD;
        uint32_t qa[32];
        {
            const uint32_t* qp = reinterpret_cast<const uint32_t*>(q + rowoff) + t;
#pragma unroll
            for (int i = 0; i < 16; i++)
                asm volatile("ld.global.b32 %0, [%1];" : "=r"(qa[2 * i]) : "l"(qp + 4 * i) : "memory");
        }
        asm volatile("bar.sync 0, 384;" ::: "memory");
        asm volatile("setmaxnreg.inc.sync.aligned.u32 232;");

        constexpr float kScaleLog2 = 0.08838834764831845f * 1.4426950408889634f;
        const uint32_t full0 = bars + wg * (kSlots * 8);
        const uint32_t empty0 = full0 + 2 * kSlots * 8;
        const uint32_t ring_lo = ((sbase + wg * kRingBytes) & 0x3FFFF) >> 4;
        const uint32_t lane0 = (lane == 0);
        const uint32_t todd = __shfl_sync(0xffffffffu, (uint32_t)(t & 1), lane);
        const uint32_t ooff = __shfl_sync(0xffffffffu, (uint32_t)rowoff * 2 + (t & 1) * 16 + (t >> 1) * 8, lane);
        const uint32_t toff = __shfl_sync(0xffffffffu, (threadIdx.x & 127) * 16, lane);

        float o[64];
        float s[32];
        uint32_t p[16];
#pragma unroll
        for (int i = 0; i < 16; i++) asm volatile("" : "=r"(qa[2 * i + 1]));
#pragma unroll
        for (int i = 0; i < 8; i++) asm volatile("" : "=r"(p[2 * i + 1]));
#pragma unroll
        for (int i = 0; i < 64; i++) o[i] = 0.f;
        float m_run = -INFINITY, l_run = 0.f;

        auto issue_qk = [&](int sl) {
            const uint32_t d = ring_lo + sl * (kStageBytes >> 4) + (1u << 16);
            wgmma_n64_first<0>(s, qa + 0, d);
            wgmma_n64_acc<2>(s, qa + 4, d);
            wgmma_n64_acc<4>(s, qa + 8, d);
            wgmma_n64_acc<6>(s, qa + 12, d);
            wgmma_n64_acc<512>(s, qa + 16, d);
            wgmma_n64_acc<514>(s, qa + 20, d);
            wgmma_n64_acc<516>(s, qa + 24, d);
            wgmma_n64_acc<518>(s, qa + 28, d);
        };
        auto issue_pv = [&](int sl) {
            const uint32_t d = ring_lo + sl * (kStageBytes >> 4) + ((8192u >> 4) << 16);
            wgmma_n128_t<0>(o, p + 0, d);
            wgmma_n128_t<128>(o, p + 4, d);
            wgmma_n128_t<256>(o, p + 8, d);
            wgmma_n128_t<384>(o, p + 12, d);
        };
        auto softmax = [&]() -> float {
            const float mx0 = fmaxf(fmaxf(s[0], s[1]), fmaxf(s[4], s[5]));
            const float mx1 = fmaxf(fmaxf(s[8], s[9]), fmaxf(s[12], s[13]));
            const float mx2 = fmaxf(fmaxf(s[16], s[17]), fmaxf(s[20], s[21]));
            const float mx3 = fmaxf(fmaxf(s[24], s[25]), fmaxf(s[28], s[29]));
            float mx = fmaxf(fmaxf(mx0, mx1), fmaxf(fmaxf(mx2, mx3), m_run));
            mx = fmaxf(mx, __shfl_xor_sync(0xffffffffu, mx, 1));
            const float m_new = fmaxf(mx, __shfl_xor_sync(0xffffffffu, mx, 2));
            const float alpha = ex2((m_run - m_new) * kScaleLog2);
            const float mb = m_new * kScaleLog2;
            m_run = m_new;
            float sum0 = 0.f, sum1 = 0.f;
#pragma unroll
            for (int i = 0; i < 8; i++) {
                s[4 * i] = ex2(fmaf(s[4 * i], kScaleLog2, -mb));
                s[4 * i + 1] = ex2(fmaf(s[4 * i + 1], kScaleLog2, -mb));
                sum0 += s[4 * i];
                sum1 += s[4 * i + 1];
            }
            l_run = l_run * alpha + (sum0 + sum1);
            return alpha;
        };
        auto pack_p = [&]() {
#pragma unroll
            for (int i = 0; i < 8; i++) p[2 * i] = pack_bf16(s[4 * i], s[4 * i + 1]);
        };
        auto pack_p_scaled = [&](float f) {
#pragma unroll
            for (int i = 0; i < 8; i++) p[2 * i] = pack_bf16(s[4 * i] * f, s[4 * i + 1] * f);
        };
        auto rescale = [&](float alpha) {
#pragma unroll
            for (int i = 0; i < 16; i++) {
                asm volatile("mul.f32 %0, %0, %1;" : "+f"(o[4 * i]) : "f"(alpha));
                asm volatile("mul.f32 %0, %0, %1;" : "+f"(o[4 * i + 1]) : "f"(alpha));
            }
        };

        int slot = 0;
        uint32_t phase = 0;
        auto advance = [&]() {
            if (++slot == kSlots) { slot = 0; phase ^= 1; }
        };
        auto do_qk = [&]() -> float {
            reg_fence(p);
            mbar_wait(full0 + 8 * slot, phase);
            wg_fence();
            issue_qk(slot);
            wg_commit();
            wg_wait<0>();
            reg_fence(s);
            mbar_arrive_pred(empty0 + 8 * slot, lane0);
            advance();
            return softmax();
        };
        auto do_pv = [&]() {
            reg_fence(o);
            reg_fence(p);
            wg_fence();
            issue_pv(slot);
            wg_commit();
            wg_wait<0>();
            reg_fence(o);
            reg_fence(p);
            mbar_arrive_pred(empty0 + 8 * slot, lane0);
            advance();
        };
#pragma unroll
        for (int i = 0; i < 8; i++) p[2 * i] = 0;
        do_qk();
        pack_p();
        float alpha_b = do_qk();
        const uint32_t pairbar = sbase + kHandOff + w4 * 8;
        const uint32_t mlrow = sbase + kMlOff + ((toff >> 6) << 3);
        float f = 1.f;
#pragma unroll 1
        for (int grp = 0;; grp++) {
            const bool last = grp == kTilesWG / 2 - 1;
            mbar_wait(full0 + 8 * slot, phase);
            do_pv();
            pack_p_scaled(f);
            rescale(alpha_b * f);
            if (last) break;
            mbar_wait(full0 + 8 * slot, phase);
            do_pv();
            rescale(do_qk());
            pack_p();
            alpha_b = do_qk();
            if (grp == kTilesWG / 2 - 2) {
                float l_tot = l_run + __shfl_xor_sync(0xffffffffu, l_run, 1);
                l_tot += __shfl_xor_sync(0xffffffffu, l_tot, 2);
                asm volatile("st.shared.v2.f32 [%0], {%1, %2};" ::"r"(mlrow + wg * 256), "f"(m_run), "f"(l_tot) : "memory");
                __syncwarp();
                mbar_arrive_pred(pairbar, lane0);
                asm volatile("bar.sync %0, 128;" ::"r"(5 + wg) : "memory");
                mbar_wait(pairbar, 0);
                float m0, l0;
                asm volatile("ld.shared.v2.f32 {%0, %1}, [%2];" : "=f"(m0), "=f"(l0) : "r"(mlrow + (wg ^ 1) * 256) : "memory");
                const float m = fmaxf(m0, m_run);
                const float a0 = ex2((m0 - m) * kScaleLog2), a1 = ex2((m_run - m) * kScaleLog2);
                f = __fdividef(a1, l0 * a0 + l_tot * a1);
            }
        }
        const uint32_t xbuf = sbase + kLastKSlot * kStageBytes + toff;
        char* op = reinterpret_cast<char*>(out) + ooff;
        reg_fence(o);
        reg_fence(p);
        mbar_wait(full0 + 8 * slot, phase);
        wg_fence();
        issue_pv(slot);
        wg_commit();

        float x[32];
        if (wg == 1) {
            asm volatile("bar.sync %0, 64;" ::"r"(1 + w4) : "memory");
#pragma unroll
            for (int i = 0; i < 8; i++) lds_f32x4(xbuf + i * 2048, x[4 * i], x[4 * i + 1], x[4 * i + 2], x[4 * i + 3]);
        }
        wg_wait<0>();
        reg_fence(o);
        reg_fence(p);
        if (wg == 0) {
#pragma unroll
            for (int i = 0; i < 8; i++) sts_f32x4(xbuf + i * 2048, o[8 * i], o[8 * i + 1], o[8 * i + 4], o[8 * i + 5]);
            asm volatile("bar.arrive %0, 64;" ::"r"(1 + w4) : "memory");
        } else {
#pragma unroll
            for (int i = 0; i < 8; i++) {
                const uint32_t r0 = pack_bf16(o[8 * i] + x[4 * i], o[8 * i + 1] + x[4 * i + 1]);
                const uint32_t r1 = pack_bf16(o[8 * i + 4] + x[4 * i + 2], o[8 * i + 5] + x[4 * i + 3]);
                const uint32_t recv = __shfl_xor_sync(0xffffffffu, todd ? r0 : r1, 1);
                *reinterpret_cast<uint2*>(op + 32 * i) = make_uint2(todd ? recv : r0, todd ? r1 : recv);
            }
        }
    }
}

typedef CUresult (*EncodeFn)(CUtensorMap*, CUtensorMapDataType, cuuint32_t, void*, const cuuint64_t*,
                             const cuuint64_t*, const cuuint32_t*, const cuuint32_t*, CUtensorMapInterleave,
                             CUtensorMapSwizzle, CUtensorMapL2promotion, CUtensorMapFloatOOBfill);

void make_kv_map(EncodeFn enc, CUtensorMap* tm, const void* ptr) {
    cuuint64_t dims[3] = {64, (cuuint64_t)kPairs * kSk, 2};
    cuuint64_t strides[2] = {kD * 2, 128};
    cuuint32_t box[3] = {64, (cuuint32_t)kTile, 2};
    cuuint32_t estr[3] = {1, 1, 1};
    enc(tm, CU_TENSOR_MAP_DATA_TYPE_BFLOAT16, 3, const_cast<void*>(ptr), dims, strides, box, estr,
        CU_TENSOR_MAP_INTERLEAVE_NONE, CU_TENSOR_MAP_SWIZZLE_128B, CU_TENSOR_MAP_L2_PROMOTION_L2_256B,
        CU_TENSOR_MAP_FLOAT_OOB_FILL_NONE);
}

}

extern "C" void kernel_launch(void* const* d_in, const int* in_sizes, int n_in, void* d_out, int out_size) {
    (void)in_sizes; (void)n_in; (void)out_size;
    static EncodeFn enc = nullptr;
    if (!enc) {
        cudaDriverEntryPointQueryResult qr;
        void* fn = nullptr;
        cudaGetDriverEntryPoint("cuTensorMapEncodeTiled", &fn, cudaEnableDefault, &qr);
        enc = (EncodeFn)fn;
        cudaFuncSetAttribute(gqa_decode_kernel, cudaFuncAttributeMaxDynamicSharedMemorySize, kSmemBytes);
    }
    CUtensorMap tmK, tmV;
    make_kv_map(enc, &tmK, d_in[1]);
    make_kv_map(enc, &tmV, d_in[2]);
    gqa_decode_kernel<<<kPairs, kThreads, kSmemBytes, cudaStreamPerThread>>>(
        tmK, tmV, (const __nv_bfloat16*)d_in[0], (__nv_bfloat16*)d_out);
}
```

```cpp
#include <cuda_runtime.h>
#include <cuda_bf16.h>
#include <cuda.h>
#include <stdint.h>

namespace {

constexpr int kB = 32, kHq = 32, kHkv = 4, kSq = 4, kSk = 2048, kD = 128;
constexpr int kRows = (kHq / kHkv) * kSq;
constexpr int kPairs = kB * kHkv;
constexpr int kTile = 64;
constexpr int kNT = kSk / kTile;
constexpr int kStageBytes = kTile * kD * 2;
constexpr int kSlots = 7;
constexpr int kWin = 6;
constexpr int kFirst = 4;
constexpr int kPaceNs = 650;
constexpr int kPaceOffNs = 40150 - 63 * kPaceNs;
constexpr int kBurstLo = 4, kBurstHi = 60;
constexpr int kTilesWG = kNT / 2;
constexpr int kLoadsWG = 2 * kTilesWG;
constexpr int kThreads = 384;
constexpr int kRingBytes = kSlots * kStageBytes;
constexpr int kMlOff = 2 * kRingBytes;
constexpr int kBarOff = kMlOff + 2 * 32 * 8;
constexpr int kHandOff = kBarOff + 4 * kSlots * 8;
constexpr int kSmemBytes = kHandOff + 32 + 1024;
constexpr int kLastKSlot = (kLoadsWG - 3) % kSlots;
static_assert(kFirst == 4, "barrier init split");
static_assert(kFirst <= kWin && kFirst <= 2 * kSlots && kSlots >= 4, "config");
static_assert(kSmemBytes <= 232448, "shared memory");

__device__ __forceinline__ uint32_t smem_u32(const void* p) { return (uint32_t)__cvta_generic_to_shared(p); }

__device__ __forceinline__ void mbar_init(uint32_t bar, uint32_t cnt) {
    asm volatile("mbarrier.init.shared::cta.b64 [%0], %1;" ::"r"(bar), "r"(cnt) : "memory");
}
__device__ __forceinline__ void mbar_expect_tx(uint32_t bar, uint32_t bytes) {
    asm volatile("mbarrier.arrive.expect_tx.shared::cta.b64 _, [%0], %1;" ::"r"(bar), "r"(bytes) : "memory");
}
__device__ __forceinline__ void mbar_arrive_pred(uint32_t bar, uint32_t pred) {
    asm volatile("{\n .reg .pred q;\n setp.ne.b32 q, %1, 0;\n @q mbarrier.arrive.shared::cta.b64 _, [%0];\n}"
                 ::"r"(bar), "r"(pred) : "memory");
}
__device__ __forceinline__ void mbar_wait(uint32_t bar, uint32_t parity) {
    asm volatile(
        "{\n"
        " .reg .pred q;\n"
        " .reg .u32 n;\n"
        " mbarrier.try_wait.parity.shared::cta.b64 q, [%0], %1;\n"
        " @q bra DONE;\n"
        " mov.u32 n, 0;\n"
        "SPIN:\n"
        " mbarrier.try_wait.parity.shared::cta.b64 q, [%0], %1;\n"
        " @q bra DONE;\n"
        " add.u32 n, n, 1;\n"
        " setp.lt.u32 q, n, 0x400000;\n"
        " @q bra SPIN;\n"
        " trap;\n"
        "DONE:\n"
        "}" ::"r"(bar), "r"(parity) : "memory");
}
__device__ __forceinline__ void tma_load_tile(uint32_t dst, const CUtensorMap* tm, int row, uint32_t bar) {
    uint64_t pol;
    asm("createpolicy.fractional.L2::evict_first.b64 %0, 1.0;" : "=l"(pol));
    asm volatile(
        "cp.async.bulk.tensor.3d.shared::cluster.global.mbarrier::complete_tx::bytes.L2::cache_hint"
        " [%0], [%1, {%3, %4, %5}], [%2], %6;"
        ::"r"(dst), "l"(tm), "r"(bar), "r"(0), "r"(row), "r"(0), "l"(pol) : "memory");
}
__device__ __forceinline__ uint32_t gtime32() {
    uint32_t t;
    asm volatile("mov.u32 %0, %globaltimer_lo;" : "=r"(t));
    return t;
}

__device__ __forceinline__ void wg_fence() { asm volatile("wgmma.fence.sync.aligned;" ::: "memory"); }
__device__ __forceinline__ void wg_commit() { asm volatile("wgmma.commit_group.sync.aligned;" ::: "memory"); }
template <int N>
__device__ __forceinline__ void wg_wait() { asm volatile("wgmma.wait_group.sync.aligned %0;" ::"n"(N) : "memory"); }

template <int N>
__device__ __forceinline__ void reg_fence(float (&r)[N]) {
#pragma unroll
    for (int i = 0; i < N; i++) asm volatile("" : "+f"(r[i])::"memory");
}
template <int N>
__device__ __forceinline__ void reg_fence(uint32_t (&r)[N]) {
#pragma unroll
    for (int i = 0; i < N; i++) asm volatile("" : "+r"(r[i])::"memory");
}

#define DESC_HI "0x40000040"

template <int OFF>
__device__ __forceinline__ void wgmma_n64_first(float (&d)[32], const uint32_t* a, uint32_t desc_lo) {
    asm volatile(
        "{\n .reg .pred p;\n .reg .b32 lo;\n .reg .b64 dd;\n setp.ne.b32 p, 0, 0;\n"
        " add.u32 lo, %36, %37;\n mov.b64 dd, {lo, " DESC_HI "};\n"
        "wgmma.mma_async.sync.aligned.m64n64k16.f32.bf16.bf16 "
        "{%0,%1,%2,%3,%4,%5,%6,%7,%8,%9,%10,%11,%12,%13,%14,%15,"
        "%16,%17,%18,%19,%20,%21,%22,%23,%24,%25,%26,%27,%28,%29,%30,%31},"
        "{%32,%33,%34,%35}, dd, p, 1, 1, 0;\n}"
        : "=f"(d[0]), "=f"(d[1]), "=f"(d[2]), "=f"(d[3]), "=f"(d[4]), "=f"(d[5]), "=f"(d[6]), "=f"(d[7]),
          "=f"(d[8]), "=f"(d[9]), "=f"(d[10]), "=f"(d[11]), "=f"(d[12]), "=f"(d[13]), "=f"(d[14]), "=f"(d[15]),
          "=f"(d[16]), "=f"(d[17]), "=f"(d[18]), "=f"(d[19]), "=f"(d[20]), "=f"(d[21]), "=f"(d[22]), "=f"(d[23]),
          "=f"(d[24]), "=f"(d[25]), "=f"(d[26]), "=f"(d[27]), "=f"(d[28]), "=f"(d[29]), "=f"(d[30]), "=f"(d[31])
        : "r"(a[0]), "r"(a[1]), "r"(a[2]), "r"(a[3]), "r"(desc_lo), "n"(OFF));
}
template <int OFF>
__device__ __forceinline__ void wgmma_n64_acc(float (&d)[32], const uint32_t* a, uint32_t desc_lo) {
    asm volatile(
        "{\n .reg .pred p;\n .reg .b32 lo;\n .reg .b64 dd;\n setp.eq.b32 p, 0, 0;\n"
        " add.u32 lo, %36, %37;\n mov.b64 dd, {lo, " DESC_HI "};\n"
        "wgmma.mma_async.sync.aligned.m64n64k16.f32.bf16.bf16 "
        "{%0,%1,%2,%3,%4,%5,%6,%7,%8,%9,%10,%11,%12,%13,%14,%15,"
        "%16,%17,%18,%19,%20,%21,%22,%23,%24,%25,%26,%27,%28,%29,%30,%31},"
        "{%32,%33,%34,%35}, dd, p, 1, 1, 0;\n}"
        : "+f"(d[0]), "+f"(d[1]), "+f"(d[2]), "+f"(d[3]), "+f"(d[4]), "+f"(d[5]), "+f"(d[6]), "+f"(d[7]),
          "+f"(d[8]), "+f"(d[9]), "+f"(d[10]), "+f"(d[11]), "+f"(d[12]), "+f"(d[13]), "+f"(d[14]), "+f"(d[15]),
          "+f"(d[16]), "+f"(d[17]), "+f"(d[18]), "+f"(d[19]), "+f"(d[20]), "+f"(d[21]), "+f"(d[22]), "+f"(d[23]),
          "+f"(d[24]), "+f"(d[25]), "+f"(d[26]), "+f"(d[27]), "+f"(d[28]), "+f"(d[29]), "+f"(d[30]), "+f"(d[31])
        : "r"(a[0]), "r"(a[1]), "r"(a[2]), "r"(a[3]), "r"(desc_lo), "n"(OFF));
}
template <int OFF>
__device__ __forceinline__ void wgmma_n128_t(float (&d)[64], const uint32_t* a, uint32_t desc_lo) {
    asm volatile(
        "{\n .reg .pred p;\n .reg .b32 lo;\n .reg .b64 dd;\n setp.eq.b32 p, 0, 0;\n"
        " add.u32 lo, %68, %69;\n mov.b64 dd, {lo, " DESC_HI "};\n"
        "wgmma.mma_async.sync.aligned.m64n128k16.f32.bf16.bf16 "
        "{%0,%1,%2,%3,%4,%5,%6,%7,%8,%9,%10,%11,%12,%13,%14,%15,"
        "%16,%17,%18,%19,%20,%21,%22,%23,%24,%25,%26,%27,%28,%29,%30,%31,"
        "%32,%33,%34,%35,%36,%37,%38,%39,%40,%41,%42,%43,%44,%45,%46,%47,"
        "%48,%49,%50,%51,%52,%53,%54,%55,%56,%57,%58,%59,%60,%61,%62,%63},"
        "{%64,%65,%66,%67}, dd, p, 1, 1, 1;\n}"
        : "+f"(d[0]), "+f"(d[1]), "+f"(d[2]), "+f"(d[3]), "+f"(d[4]), "+f"(d[5]), "+f"(d[6]), "+f"(d[7]),
          "+f"(d[8]), "+f"(d[9]), "+f"(d[10]), "+f"(d[11]), "+f"(d[12]), "+f"(d[13]), "+f"(d[14]), "+f"(d[15]),
          "+f"(d[16]), "+f"(d[17]), "+f"(d[18]), "+f"(d[19]), "+f"(d[20]), "+f"(d[21]), "+f"(d[22]), "+f"(d[23]),
          "+f"(d[24]), "+f"(d[25]), "+f"(d[26]), "+f"(d[27]), "+f"(d[28]), "+f"(d[29]), "+f"(d[30]), "+f"(d[31]),
          "+f"(d[32]), "+f"(d[33]), "+f"(d[34]), "+f"(d[35]), "+f"(d[36]), "+f"(d[37]), "+f"(d[38]), "+f"(d[39]),
          "+f"(d[40]), "+f"(d[41]), "+f"(d[42]), "+f"(d[43]), "+f"(d[44]), "+f"(d[45]), "+f"(d[46]), "+f"(d[47]),
          "+f"(d[48]), "+f"(d[49]), "+f"(d[50]), "+f"(d[51]), "+f"(d[52]), "+f"(d[53]), "+f"(d[54]), "+f"(d[55]),
          "+f"(d[56]), "+f"(d[57]), "+f"(d[58]), "+f"(d[59]), "+f"(d[60]), "+f"(d[61]), "+f"(d[62]), "+f"(d[63])
        : "r"(a[0]), "r"(a[1]), "r"(a[2]), "r"(a[3]), "r"(desc_lo), "n"(OFF));
}

__device__ __forceinline__ float ex2(float x) {
    float y;
    asm("ex2.approx.ftz.f32 %0, %1;" : "=f"(y) : "f"(x));
    return y;
}
__device__ __forceinline__ uint32_t pack_bf16(float lo, float hi) {
    uint32_t r;
    asm("cvt.rn.bf16x2.f32 %0, %1, %2;" : "=r"(r) : "f"(hi), "f"(lo));
    return r;
}
__device__ __forceinline__ void lds_f32x4(uint32_t addr, float& a, float& b, float& c, float& d) {
    asm volatile("ld.shared.v4.f32 {%0, %1, %2, %3}, [%4];" : "=f"(a), "=f"(b), "=f"(c), "=f"(d) : "r"(addr) : "memory");
}
__device__ __forceinline__ void sts_f32x4(uint32_t addr, float a, float b, float c, float d) {
    asm volatile("st.shared.v4.f32 [%0], {%1, %2, %3, %4};" ::"r"(addr), "f"(a), "f"(b), "f"(c), "f"(d) : "memory");
}

__host__ __device__ constexpr int ring_of(int n) { return (n >> 1) & 1; }
__host__ __device__ constexpr int local_of(int n) { return ((n >> 2) << 1) | (n & 1); }
__device__ __forceinline__ void issue_load(int n, uint32_t dst, uint32_t bar, const CUtensorMap* tmK,
                                           const CUtensorMap* tmV, int row0) {
    const int tile = ((n >> 3) << 2) | (n & 3);
    mbar_expect_tx(bar, kStageBytes);
    tma_load_tile(dst, (n & 4) ? tmV : tmK, row0 + tile * kTile, bar);
}

__global__ void __launch_bounds__(kThreads, 1)
gqa_decode_kernel(const __grid_constant__ CUtensorMap tmK, const __grid_constant__ CUtensorMap tmV,
                  const __nv_bfloat16* __restrict__ q, __nv_bfloat16* __restrict__ out) {
    extern __shared__ uint8_t smem_raw[];
    const int pair = (((blockIdx.x + (blockIdx.x >> 3)) & 7) << 4) | (blockIdx.x >> 3);
    const uint32_t sbase = (smem_u32(smem_raw) + 1023u) & ~1023u;
    const uint32_t bars = sbase + kBarOff;
    const int row0 = pair * kSk;

    const bool p_active = threadIdx.x == 0;
    uint32_t t_start = 0;
    if (p_active) {
#pragma unroll
        for (int n = 0; n < kFirst; n++) mbar_init(bars + 8 * (ring_of(n) * kSlots + local_of(n)), 1);
        asm volatile("fence.mbarrier_init.release.cluster;" ::: "memory");
        issue_load(0, sbase, bars, &tmK, &tmV, row0);
        t_start = gtime32();
#pragma unroll
        for (int n = 1; n < kFirst; n++) {
            const int slot = ring_of(n) * kSlots + local_of(n);
            issue_load(n, sbase + slot * kStageBytes, bars + 8 * slot, &tmK, &tmV, row0);
        }
#pragma unroll
        for (int s = 0; s < 2 * kSlots; s++)
            if (s % kSlots >= 2) mbar_init(bars + 8 * s, 1);
#pragma unroll
        for (int s = 0; s < 2 * kSlots; s++) mbar_init(bars + 2 * kSlots * 8 + 8 * s, 4);
#pragma unroll
        for (int s = 0; s < 4; s++) mbar_init(sbase + kHandOff + 8 * s, 64);
        asm volatile("fence.mbarrier_init.release.cluster;" ::: "memory");
    }

    const int warp = __shfl_sync(0xffffffffu, (int)(threadIdx.x >> 5), 0);
    if (warp < 4) {
        __syncwarp();
        asm volatile("bar.arrive 0, 384;" ::: "memory");
        asm volatile("setmaxnreg.dec.sync.aligned.u32 40;");
        if (p_active) {
#pragma unroll 1
            for (int n = kFirst; n < 2 * kLoadsWG; n++) {
                const int m = n - kWin;
                if (m >= 0) {
                    const int wi = local_of(m), wq = wi / kSlots;
                    mbar_wait(bars + 8 * (wi - wq * kSlots + ring_of(m) * kSlots), wq & 1);
                }
                const int i = local_of(n), iq = i / kSlots, slot = i - iq * kSlots + ring_of(n) * kSlots;
                mbar_wait(bars + 2 * kSlots * 8 + 8 * slot, (iq & 1) ^ 1);
                const int turn = (n >= kBurstLo && n < kBurstHi) ? (n & ~3) + (pair >> 5) : n;
                const uint32_t due = t_start + (uint32_t)(kPaceOffNs + turn * kPaceNs);
                for (int it = 0; it < 4096 && (int)(gtime32() - due) < 0; it++) { }
                issue_load(n, sbase + slot * kStageBytes, bars + 8 * slot, &tmK, &tmV, row0);
            }
        }
    } else {
        const int wg = (warp >> 2) - 1;
        const int w4 = warp & 3;
        const int lane = threadIdx.x & 31;
        const int g = lane >> 2, t = lane & 3;

        const size_t rowoff = ((size_t)pair * kRows + w4 * 8 + g) * kD;
        uint32_t qa[32];
        {
            const uint32_t* qp = reinterpret_cast<const uint32_t*>(q + rowoff) + t;
#pragma unroll
            for (int i = 0; i < 16; i++)
                asm volatile("ld.global.b32 %0, [%1];" : "=r"(qa[2 * i]) : "l"(qp + 4 * i) : "memory");
        }
        asm volatile("bar.sync 0, 384;" ::: "memory");
        asm volatile("setmaxnreg.inc.sync.aligned.u32 232;");

        constexpr float kScaleLog2 = 0.08838834764831845f * 1.4426950408889634f;
        const uint32_t full0 = bars + wg * (kSlots * 8);
        const uint32_t empty0 = full0 + 2 * kSlots * 8;
        const uint32_t ring_lo = ((sbase + wg * kRingBytes) & 0x3FFFF) >> 4;
        const uint32_t lane0 = (lane == 0);
        const uint32_t todd = __shfl_sync(0xffffffffu, (uint32_t)(t & 1), lane);
        const uint32_t ooff = __shfl_sync(0xffffffffu, (uint32_t)rowoff * 2 + (t & 1) * 16 + (t >> 1) * 8, lane);
        const uint32_t toff = __shfl_sync(0xffffffffu, (threadIdx.x & 127) * 16, lane);

        float o[64];
        float s[32];
        uint32_t p[16];
#pragma unroll
        for (int i = 0; i < 16; i++) asm volatile("" : "=r"(qa[2 * i + 1]));
#pragma unroll
        for (int i = 0; i < 8; i++) asm volatile("" : "=r"(p[2 * i + 1]));
#pragma unroll
        for (int i = 0; i < 64; i++) o[i] = 0.f;
        float m_run = -INFINITY, l_run = 0.f;

        auto issue_qk = [&](int sl) {
            const uint32_t d = ring_lo + sl * (kStageBytes >> 4) + (1u << 16);
            wgmma_n64_first<0>(s, qa + 0, d);
            wgmma_n64_acc<2>(s, qa + 4, d);
            wgmma_n64_acc<4>(s, qa + 8, d);
            wgmma_n64_acc<6>(s, qa + 12, d);
            wgmma_n64_acc<512>(s, qa + 16, d);
            wgmma_n64_acc<514>(s, qa + 20, d);
            wgmma_n64_acc<516>(s, qa + 24, d);
            wgmma_n64_acc<518>(s, qa + 28, d);
        };
        auto issue_pv = [&](int sl) {
            const uint32_t d = ring_lo + sl * (kStageBytes >> 4) + ((8192u >> 4) << 16);
            wgmma_n128_t<0>(o, p + 0, d);
            wgmma_n128_t<128>(o, p + 4, d);
            wgmma_n128_t<256>(o, p + 8, d);
            wgmma_n128_t<384>(o, p + 12, d);
        };
        auto softmax = [&]() -> float {
            const float mx0 = fmaxf(fmaxf(s[0], s[1]), fmaxf(s[4], s[5]));
            const float mx1 = fmaxf(fmaxf(s[8], s[9]), fmaxf(s[12], s[13]));
            const float mx2 = fmaxf(fmaxf(s[16], s[17]), fmaxf(s[20], s[21]));
            const float mx3 = fmaxf(fmaxf(s[24], s[25]), fmaxf(s[28], s[29]));
            float mx = fmaxf(fmaxf(mx0, mx1), fmaxf(fmaxf(mx2, mx3), m_run));
            mx = fmaxf(mx, __shfl_xor_sync(0xffffffffu, mx, 1));
            const float m_new = fmaxf(mx, __shfl_xor_sync(0xffffffffu, mx, 2));
            const float alpha = ex2((m_run - m_new) * kScaleLog2);
            const float mb = m_new * kScaleLog2;
            m_run = m_new;
            float sum0 = 0.f, sum1 = 0.f;
#pragma unroll
            for (int i = 0; i < 8; i++) {
                s[4 * i] = ex2(fmaf(s[4 * i], kScaleLog2, -mb));
                s[4 * i + 1] = ex2(fmaf(s[4 * i + 1], kScaleLog2, -mb));
                sum0 += s[4 * i];
                sum1 += s[4 * i + 1];
            }
            l_run = l_run * alpha + (sum0 + sum1);
            return alpha;
        };
        auto pack_p = [&]() {
#pragma unroll
            for (int i = 0; i < 8; i++) p[2 * i] = pack_bf16(s[4 * i], s[4 * i + 1]);
        };
        auto pack_p_scaled = [&](float f) {
#pragma unroll
            for (int i = 0; i < 8; i++) p[2 * i] = pack_bf16(s[4 * i] * f, s[4 * i + 1] * f);
        };
        auto rescale = [&](float alpha) {
#pragma unroll
            for (int i = 0; i < 16; i++) {
                asm volatile("mul.f32 %0, %0, %1;" : "+f"(o[4 * i]) : "f"(alpha));
                asm volatile("mul.f32 %0, %0, %1;" : "+f"(o[4 * i + 1]) : "f"(alpha));
            }
        };

        int slot = 0;
        uint32_t phase = 0;
        auto advance = [&]() {
            if (++slot == kSlots) { slot = 0; phase ^= 1; }
        };
        auto do_qk = [&]() -> float {
            reg_fence(p);
            mbar_wait(full0 + 8 * slot, phase);
            wg_fence();
            issue_qk(slot);
            wg_commit();
            wg_wait<0>();
            reg_fence(s);
            mbar_arrive_pred(empty0 + 8 * slot, lane0);
            advance();
            return softmax();
        };
        auto do_pv = [&]() {
            reg_fence(o);
            reg_fence(p);
            wg_fence();
            issue_pv(slot);
            wg_commit();
            wg_wait<0>();
            reg_fence(o);
            reg_fence(p);
            mbar_arrive_pred(empty0 + 8 * slot, lane0);
            advance();
        };
#pragma unroll
        for (int i = 0; i < 8; i++) p[2 * i] = 0;
        do_qk();
        pack_p();
        float alpha_b = do_qk();
        const uint32_t pairbar = sbase + kHandOff + w4 * 8;
        const uint32_t mlrow = sbase + kMlOff + ((toff >> 6) << 3);
        float f = 1.f;
#pragma unroll 1
        for (int grp = 0;; grp++) {
            const bool last = grp == kTilesWG / 2 - 1;
            mbar_wait(full0 + 8 * slot, phase);
            do_pv();
            pack_p_scaled(f);
            rescale(alpha_b * f);
            if (last) break;
            mbar_wait(full0 + 8 * slot, phase);
            do_pv();
            rescale(do_qk());
            pack_p();
            alpha_b = do_qk();
            if (grp == kTilesWG / 2 - 2) {
                float l_tot = l_run + __shfl_xor_sync(0xffffffffu, l_run, 1);
                l_tot += __shfl_xor_sync(0xffffffffu, l_tot, 2);
                asm volatile("st.shared.v2.f32 [%0], {%1, %2};" ::"r"(mlrow + wg * 256), "f"(m_run), "f"(l_tot) : "memory");
                mbar_arrive_pred(pairbar, 1);
                asm volatile("bar.sync %0, 128;" ::"r"(5 + wg) : "memory");
                mbar_wait(pairbar, 0);
                float m0, l0;
                asm volatile("ld.shared.v2.f32 {%0, %1}, [%2];" : "=f"(m0), "=f"(l0) : "r"(mlrow + (wg ^ 1) * 256) : "memory");
                const float m = fmaxf(m0, m_run);
                const float a0 = ex2((m0 - m) * kScaleLog2), a1 = ex2((m_run - m) * kScaleLog2);
                f = __fdividef(a1, l0 * a0 + l_tot * a1);
            }
        }
        const uint32_t xbuf = sbase + kLastKSlot * kStageBytes + toff;
        char* op = reinterpret_cast<char*>(out) + ooff;
        reg_fence(o);
        reg_fence(p);
        mbar_wait(full0 + 8 * slot, phase);
        wg_fence();
        issue_pv(slot);
        wg_commit();

        float x[32];
        if (wg == 1) {
            asm volatile("bar.sync %0, 64;" ::"r"(1 + w4) : "memory");
#pragma unroll
            for (int i = 0; i < 8; i++) lds_f32x4(xbuf + i * 2048, x[4 * i], x[4 * i + 1], x[4 * i + 2], x[4 * i + 3]);
        }
        wg_wait<0>();
        reg_fence(o);
        reg_fence(p);
        if (wg == 0) {
#pragma unroll
            for (int i = 0; i < 8; i++) sts_f32x4(xbuf + i * 2048, o[8 * i], o[8 * i + 1], o[8 * i + 4], o[8 * i + 5]);
            asm volatile("bar.arrive %0, 64;" ::"r"(1 + w4) : "memory");
        } else {
#pragma unroll
            for (int i = 0; i < 8; i++) {
                const uint32_t r0 = pack_bf16(o[8 * i] + x[4 * i], o[8 * i + 1] + x[4 * i + 1]);
                const uint32_t r1 = pack_bf16(o[8 * i + 4] + x[4 * i + 2], o[8 * i + 5] + x[4 * i + 3]);
                const uint32_t recv = __shfl_xor_sync(0xffffffffu, todd ? r0 : r1, 1);
                __stcg(reinterpret_cast<uint2*>(op + 32 * i), make_uint2(todd ? recv : r0, todd ? r1 : recv));
            }
        }
    }
}

typedef CUresult (*EncodeFn)(CUtensorMap*, CUtensorMapDataType, cuuint32_t, void*, const cuuint64_t*,
                             const cuuint64_t*, const cuuint32_t*, const cuuint32_t*, CUtensorMapInterleave,
                             CUtensorMapSwizzle, CUtensorMapL2promotion, CUtensorMapFloatOOBfill);

void make_kv_map(EncodeFn enc, CUtensorMap* tm, const void* ptr) {
    cuuint64_t dims[3] = {64, (cuuint64_t)kPairs * kSk, 2};
    cuuint64_t strides[2] = {kD * 2, 128};
    cuuint32_t box[3] = {64, (cuuint32_t)kTile, 2};
    cuuint32_t estr[3] = {1, 1, 1};
    enc(tm, CU_TENSOR_MAP_DATA_TYPE_BFLOAT16, 3, const_cast<void*>(ptr), dims, strides, box, estr,
        CU_TENSOR_MAP_INTERLEAVE_NONE, CU_TENSOR_MAP_SWIZZLE_128B, CU_TENSOR_MAP_L2_PROMOTION_L2_256B,
        CU_TENSOR_MAP_FLOAT_OOB_FILL_NONE);
}

}

extern "C" void kernel_launch(void* const* d_in, const int* in_sizes, int n_in, void* d_out, int out_size) {
    (void)in_sizes; (void)n_in; (void)out_size;
    static EncodeFn enc = nullptr;
    if (!enc) {
        cudaDriverEntryPointQueryResult qr;
        void* fn = nullptr;
        cudaGetDriverEntryPoint("cuTensorMapEncodeTiled", &fn, cudaEnableDefault, &qr);
        enc = (EncodeFn)fn;
        cudaFuncSetAttribute(gqa_decode_kernel, cudaFuncAttributeMaxDynamicSharedMemorySize, kSmemBytes);
    }
    CUtensorMap tmK, tmV;
    make_kv_map(enc, &tmK, d_in[1]);
    make_kv_map(enc, &tmV, d_in[2]);
    gqa_decode_kernel<<<kPairs, kThreads, kSmemBytes, cudaStreamPerThread>>>(
        tmK, tmV, (const __nv_bfloat16*)d_in[0], (__nv_bfloat16*)d_out);
}
```

```cpp
#include <cuda_runtime.h>
#include <cuda_bf16.h>
#include <cuda.h>
#include <stdint.h>

namespace {

constexpr int kB = 32, kHq = 32, kHkv = 4, kSq = 4, kSk = 2048, kD = 128;
constexpr int kRows = (kHq / kHkv) * kSq;
constexpr int kPairs = kB * kHkv;
constexpr int kTile = 64;
constexpr int kNT = kSk / kTile;
constexpr int kStageBytes = kTile * kD * 2;
constexpr int kSlots = 7;
constexpr int kWin = 6;
constexpr int kFirst = 4;
constexpr int kPaceNs = 641;
constexpr int kPaceOffNs = 39850 - 63 * kPaceNs;
constexpr int kBurstLo = 4, kBurstHi = 60;
constexpr int kTilesWG = kNT / 2;
constexpr int kLoadsWG = 2 * kTilesWG;
constexpr int kThreads = 384;
constexpr int kRingBytes = kSlots * kStageBytes;
constexpr int kMlOff = 2 * kRingBytes;
constexpr int kBarOff = kMlOff + 2 * 32 * 8;
constexpr int kMlBarOff = kBarOff + 4 * kSlots * 8;
constexpr int kHandOff = kMlBarOff + 8 * 8;
constexpr int kSmemBytes = kHandOff + 32 + 1024;
constexpr int kLastKSlot = (kLoadsWG - 5) % kSlots;
static_assert(kFirst == 4 && kSlots == 7, "the last two K slots (5, 6) must not be reloaded by the last V run (0..3)");
static_assert(kFirst <= kWin && kFirst <= 2 * kSlots && kSlots >= 4, "config");
static_assert(kSmemBytes <= 232448, "shared memory");

__device__ __forceinline__ uint32_t smem_u32(const void* p) { return (uint32_t)__cvta_generic_to_shared(p); }

__device__ __forceinline__ void mbar_init(uint32_t bar, uint32_t cnt) {
    asm volatile("mbarrier.init.shared::cta.b64 [%0], %1;" ::"r"(bar), "r"(cnt) : "memory");
}
__device__ __forceinline__ void mbar_expect_tx(uint32_t bar, uint32_t bytes) {
    asm volatile("mbarrier.arrive.expect_tx.shared::cta.b64 _, [%0], %1;" ::"r"(bar), "r"(bytes) : "memory");
}
__device__ __forceinline__ void mbar_arrive_pred(uint32_t bar, uint32_t pred) {
    asm volatile("{\n .reg .pred q;\n setp.ne.b32 q, %1, 0;\n @q mbarrier.arrive.shared::cta.b64 _, [%0];\n}"
                 ::"r"(bar), "r"(pred) : "memory");
}
__device__ __forceinline__ void mbar_wait(uint32_t bar, uint32_t parity) {
    asm volatile(
        "{\n"
        " .reg .pred q;\n"
        " .reg .u32 n;\n"
        " mbarrier.try_wait.parity.shared::cta.b64 q, [%0], %1;\n"
        " @q bra DONE;\n"
        " mov.u32 n, 0;\n"
        "SPIN:\n"
        " mbarrier.try_wait.parity.shared::cta.b64 q, [%0], %1;\n"
        " @q bra DONE;\n"
        " add.u32 n, n, 1;\n"
        " setp.lt.u32 q, n, 0x400000;\n"
        " @q bra SPIN;\n"
        " trap;\n"
        "DONE:\n"
        "}" ::"r"(bar), "r"(parity) : "memory");
}
__device__ __forceinline__ void tma_load_tile(uint32_t dst, const CUtensorMap* tm, int row, uint32_t bar) {
    uint64_t pol;
    asm("createpolicy.fractional.L2::evict_first.b64 %0, 1.0;" : "=l"(pol));
    asm volatile(
        "cp.async.bulk.tensor.3d.shared::cluster.global.mbarrier::complete_tx::bytes.L2::cache_hint"
        " [%0], [%1, {%3, %4, %5}], [%2], %6;"
        ::"r"(dst), "l"(tm), "r"(bar), "r"(0), "r"(row), "r"(0), "l"(pol) : "memory");
}
__device__ __forceinline__ uint32_t gtime32() {
    uint32_t t;
    asm volatile("mov.u32 %0, %globaltimer_lo;" : "=r"(t));
    return t;
}

__device__ __forceinline__ void wg_fence() { asm volatile("wgmma.fence.sync.aligned;" ::: "memory"); }
__device__ __forceinline__ void wg_commit() { asm volatile("wgmma.commit_group.sync.aligned;" ::: "memory"); }
template <int N>
__device__ __forceinline__ void wg_wait() { asm volatile("wgmma.wait_group.sync.aligned %0;" ::"n"(N) : "memory"); }

template <int N>
__device__ __forceinline__ void reg_fence(float (&r)[N]) {
#pragma unroll
    for (int i = 0; i < N; i++) asm volatile("" : "+f"(r[i])::"memory");
}
template <int N>
__device__ __forceinline__ void reg_fence(uint32_t (&r)[N]) {
#pragma unroll
    for (int i = 0; i < N; i++) asm volatile("" : "+r"(r[i])::"memory");
}

#define DESC_HI "0x40000040"

template <int OFF>
__device__ __forceinline__ void wgmma_n64_first(float (&d)[32], const uint32_t* a, uint32_t desc_lo) {
    asm volatile(
        "{\n .reg .pred p;\n .reg .b32 lo;\n .reg .b64 dd;\n setp.ne.b32 p, 0, 0;\n"
        " add.u32 lo, %36, %37;\n mov.b64 dd, {lo, " DESC_HI "};\n"
        "wgmma.mma_async.sync.aligned.m64n64k16.f32.bf16.bf16 "
        "{%0,%1,%2,%3,%4,%5,%6,%7,%8,%9,%10,%11,%12,%13,%14,%15,"
        "%16,%17,%18,%19,%20,%21,%22,%23,%24,%25,%26,%27,%28,%29,%30,%31},"
        "{%32,%33,%34,%35}, dd, p, 1, 1, 0;\n}"
        : "=f"(d[0]), "=f"(d[1]), "=f"(d[2]), "=f"(d[3]), "=f"(d[4]), "=f"(d[5]), "=f"(d[6]), "=f"(d[7]),
          "=f"(d[8]), "=f"(d[9]), "=f"(d[10]), "=f"(d[11]), "=f"(d[12]), "=f"(d[13]), "=f"(d[14]), "=f"(d[15]),
          "=f"(d[16]), "=f"(d[17]), "=f"(d[18]), "=f"(d[19]), "=f"(d[20]), "=f"(d[21]), "=f"(d[22]), "=f"(d[23]),
          "=f"(d[24]), "=f"(d[25]), "=f"(d[26]), "=f"(d[27]), "=f"(d[28]), "=f"(d[29]), "=f"(d[30]), "=f"(d[31])
        : "r"(a[0]), "r"(a[1]), "r"(a[2]), "r"(a[3]), "r"(desc_lo), "n"(OFF));
}
template <int OFF>
__device__ __forceinline__ void wgmma_n64_acc(float (&d)[32], const uint32_t* a, uint32_t desc_lo) {
    asm volatile(
        "{\n .reg .pred p;\n .reg .b32 lo;\n .reg .b64 dd;\n setp.eq.b32 p, 0, 0;\n"
        " add.u32 lo, %36, %37;\n mov.b64 dd, {lo, " DESC_HI "};\n"
        "wgmma.mma_async.sync.aligned.m64n64k16.f32.bf16.bf16 "
        "{%0,%1,%2,%3,%4,%5,%6,%7,%8,%9,%10,%11,%12,%13,%14,%15,"
        "%16,%17,%18,%19,%20,%21,%22,%23,%24,%25,%26,%27,%28,%29,%30,%31},"
        "{%32,%33,%34,%35}, dd, p, 1, 1, 0;\n}"
        : "+f"(d[0]), "+f"(d[1]), "+f"(d[2]), "+f"(d[3]), "+f"(d[4]), "+f"(d[5]), "+f"(d[6]), "+f"(d[7]),
          "+f"(d[8]), "+f"(d[9]), "+f"(d[10]), "+f"(d[11]), "+f"(d[12]), "+f"(d[13]), "+f"(d[14]), "+f"(d[15]),
          "+f"(d[16]), "+f"(d[17]), "+f"(d[18]), "+f"(d[19]), "+f"(d[20]), "+f"(d[21]), "+f"(d[22]), "+f"(d[23]),
          "+f"(d[24]), "+f"(d[25]), "+f"(d[26]), "+f"(d[27]), "+f"(d[28]), "+f"(d[29]), "+f"(d[30]), "+f"(d[31])
        : "r"(a[0]), "r"(a[1]), "r"(a[2]), "r"(a[3]), "r"(desc_lo), "n"(OFF));
}
template <int OFF>
__device__ __forceinline__ void wgmma_n128_t(float (&d)[64], const uint32_t* a, uint32_t desc_lo) {
    asm volatile(
        "{\n .reg .pred p;\n .reg .b32 lo;\n .reg .b64 dd;\n setp.eq.b32 p, 0, 0;\n"
        " add.u32 lo, %68, %69;\n mov.b64 dd, {lo, " DESC_HI "};\n"
        "wgmma.mma_async.sync.aligned.m64n128k16.f32.bf16.bf16 "
        "{%0,%1,%2,%3,%4,%5,%6,%7,%8,%9,%10,%11,%12,%13,%14,%15,"
        "%16,%17,%18,%19,%20,%21,%22,%23,%24,%25,%26,%27,%28,%29,%30,%31,"
        "%32,%33,%34,%35,%36,%37,%38,%39,%40,%41,%42,%43,%44,%45,%46,%47,"
        "%48,%49,%50,%51,%52,%53,%54,%55,%56,%57,%58,%59,%60,%61,%62,%63},"
        "{%64,%65,%66,%67}, dd, p, 1, 1, 1;\n}"
        : "+f"(d[0]), "+f"(d[1]), "+f"(d[2]), "+f"(d[3]), "+f"(d[4]), "+f"(d[5]), "+f"(d[6]), "+f"(d[7]),
          "+f"(d[8]), "+f"(d[9]), "+f"(d[10]), "+f"(d[11]), "+f"(d[12]), "+f"(d[13]), "+f"(d[14]), "+f"(d[15]),
          "+f"(d[16]), "+f"(d[17]), "+f"(d[18]), "+f"(d[19]), "+f"(d[20]), "+f"(d[21]), "+f"(d[22]), "+f"(d[23]),
          "+f"(d[24]), "+f"(d[25]), "+f"(d[26]), "+f"(d[27]), "+f"(d[28]), "+f"(d[29]), "+f"(d[30]), "+f"(d[31]),
          "+f"(d[32]), "+f"(d[33]), "+f"(d[34]), "+f"(d[35]), "+f"(d[36]), "+f"(d[37]), "+f"(d[38]), "+f"(d[39]),
          "+f"(d[40]), "+f"(d[41]), "+f"(d[42]), "+f"(d[43]), "+f"(d[44]), "+f"(d[45]), "+f"(d[46]), "+f"(d[47]),
          "+f"(d[48]), "+f"(d[49]), "+f"(d[50]), "+f"(d[51]), "+f"(d[52]), "+f"(d[53]), "+f"(d[54]), "+f"(d[55]),
          "+f"(d[56]), "+f"(d[57]), "+f"(d[58]), "+f"(d[59]), "+f"(d[60]), "+f"(d[61]), "+f"(d[62]), "+f"(d[63])
        : "r"(a[0]), "r"(a[1]), "r"(a[2]), "r"(a[3]), "r"(desc_lo), "n"(OFF));
}

__device__ __forceinline__ float ex2(float x) {
    float y;
    asm("ex2.approx.ftz.f32 %0, %1;" : "=f"(y) : "f"(x));
    return y;
}
__device__ __forceinline__ uint32_t pack_bf16(float lo, float hi) {
    uint32_t r;
    asm("cvt.rn.bf16x2.f32 %0, %1, %2;" : "=r"(r) : "f"(hi), "f"(lo));
    return r;
}
__device__ __forceinline__ void lds_f32x4(uint32_t addr, float& a, float& b, float& c, float& d) {
    asm volatile("ld.shared.v4.f32 {%0, %1, %2, %3}, [%4];" : "=f"(a), "=f"(b), "=f"(c), "=f"(d) : "r"(addr) : "memory");
}

__device__ __forceinline__ int ring_of(int n, int rank) { return ((n >> 2) & 1) ^ (n >= 56 ? rank : 0); }
__device__ __forceinline__ int local_of(int n) { return ((n >> 4) << 3) | ((n >> 1) & 4) | (n & 3); }
__device__ __forceinline__ void issue_load(int n, int ring, uint32_t dst, uint32_t bar, const CUtensorMap* tmK,
                                           const CUtensorMap* tmV, int row0) {
    mbar_expect_tx(bar, kStageBytes);
    tma_load_tile(dst, (n & 8) ? tmV : tmK, row0 + ring * (64 * kSk) + (((n >> 4) << 2) | (n & 3)) * kTile, bar);
}
__device__ __forceinline__ uint32_t map_to_cta(uint32_t addr, uint32_t rank) {
    uint32_t r;
    asm("mapa.shared::cluster.u32 %0, %1, %2;" : "=r"(r) : "r"(addr), "r"(rank));
    return r;
}
__device__ __forceinline__ void mbar_wait_cluster(uint32_t bar, uint32_t parity) {
    asm volatile(
        "{\n"
        " .reg .pred q;\n"
        " .reg .u32 n;\n"
        " mov.u32 n, 0;\n"
        "SPIN:\n"
        " mbarrier.try_wait.parity.acquire.cluster.shared::cta.b64 q, [%0], %1;\n"
        " @q bra DONE;\n"
        " add.u32 n, n, 1;\n"
        " setp.lt.u32 q, n, 0x400000;\n"
        " @q bra SPIN;\n"
        " trap;\n"
        "DONE:\n"
        "}" ::"r"(bar), "r"(parity) : "memory");
}

__global__ void __cluster_dims__(2, 1, 1) __launch_bounds__(kThreads, 1)
gqa_decode_kernel(const __grid_constant__ CUtensorMap tmK, const __grid_constant__ CUtensorMap tmV,
                  const __nv_bfloat16* __restrict__ q, __nv_bfloat16* __restrict__ out) {
    extern __shared__ uint8_t smem_raw[];
    const int rank = blockIdx.x & 1;
    const int kc = blockIdx.x >> 1;
    const int phase4 = (kc + (kc >> 2)) & 3;
    const int c = phase4 * 16 + (kc >> 2);
    const uint32_t sbase = (smem_u32(smem_raw) + 1023u) & ~1023u;
    const uint32_t bars = sbase + kBarOff;
    const int row0 = c * kSk + rank * (kSk / 2);

    const bool p_active = threadIdx.x == 0;
    uint32_t t_start = 0;
    if (p_active) {
#pragma unroll
        for (int n = 0; n < kFirst; n++) mbar_init(bars + 8 * n, 1);
        asm volatile("fence.mbarrier_init.release.cluster;" ::: "memory");
        issue_load(0, 0, sbase, bars, &tmK, &tmV, row0);
        t_start = gtime32();
#pragma unroll
        for (int n = 1; n < kFirst; n++) issue_load(n, 0, sbase + n * kStageBytes, bars + 8 * n, &tmK, &tmV, row0);
#pragma unroll
        for (int s = kFirst; s < 2 * kSlots; s++) mbar_init(bars + 8 * s, 1);
#pragma unroll
        for (int s = 0; s < 2 * kSlots; s++) mbar_init(bars + 2 * kSlots * 8 + 8 * s, 4);
#pragma unroll
        for (int s = 0; s < 12; s++) {
            mbar_init(sbase + kMlBarOff + 8 * s, 1);
            mbar_expect_tx(sbase + kMlBarOff + 8 * s, s < 8 ? 8 * 8 : 32 * 128);
        }
        asm volatile("fence.mbarrier_init.release.cluster;" ::: "memory");
    }

    const int warp = __shfl_sync(0xffffffffu, (int)(threadIdx.x >> 5), 0);
    if (warp < 4) {
        __syncwarp();
        asm volatile("bar.arrive 0, 384;" ::: "memory");
        asm volatile("barrier.cluster.arrive.relaxed.aligned;" ::: "memory");
        asm volatile("setmaxnreg.dec.sync.aligned.u32 40;");
        if (p_active) {
#pragma unroll 1
            for (int n = kFirst; n < 2 * kLoadsWG; n++) {
                const int m = n - kWin;
                if (m >= 0) {
                    const int wi = local_of(m), wq = wi / kSlots;
                    mbar_wait(bars + 8 * (wi - wq * kSlots + ring_of(m, rank) * kSlots), wq & 1);
                }
                const int ring = ring_of(n, rank);
                const int i = local_of(n), iq = i / kSlots, slot = i - iq * kSlots + ring * kSlots;
                mbar_wait(bars + 2 * kSlots * 8 + 8 * slot, (iq & 1) ^ 1);
                const int turn = (n >= kBurstLo && n < kBurstHi) ? (n & ~3) + phase4 : n;
                const uint32_t due = t_start + (uint32_t)(kPaceOffNs + turn * kPaceNs);
                for (int it = 0; it < 4096 && (int)(gtime32() - due) < 0; it++) { }
                issue_load(n, ring, sbase + slot * kStageBytes, bars + 8 * slot, &tmK, &tmV, row0);
            }
        }
    } else {
        const int wg = (warp >> 2) - 1;
        const int w4 = warp & 3;
        const int lane = threadIdx.x & 31;
        const int g = lane >> 2, t = lane & 3;

        const size_t rowoff = ((size_t)(c + 64 * wg) * kRows + w4 * 8 + g) * kD;
        uint32_t qa[32];
        {
            const uint32_t* qp = reinterpret_cast<const uint32_t*>(q + rowoff) + t;
#pragma unroll
            for (int i = 0; i < 16; i++)
                asm volatile("ld.global.b32 %0, [%1];" : "=r"(qa[2 * i]) : "l"(qp + 4 * i) : "memory");
        }
        asm volatile("bar.sync 0, 384;" ::: "memory");
        asm volatile("barrier.cluster.arrive.relaxed.aligned;" ::: "memory");
        asm volatile("setmaxnreg.inc.sync.aligned.u32 232;");

        constexpr float kScaleLog2 = 0.08838834764831845f * 1.4426950408889634f;
        const uint32_t full0 = bars + wg * (kSlots * 8);
        const uint32_t empty0 = full0 + 2 * kSlots * 8;
        const uint32_t ring_lo = ((sbase + wg * kRingBytes) & 0x3FFFF) >> 4;
        const uint32_t lane0 = (lane == 0);
        const uint32_t toff = (threadIdx.x & 127) * 16;

        float o[64];
        float s[32];
        uint32_t p0[16], p1[16], p2[16], p3[16];
#pragma unroll
        for (int i = 0; i < 16; i++) asm volatile("" : "=r"(qa[2 * i + 1]));
#pragma unroll
        for (int i = 0; i < 64; i++) o[i] = 0.f;
        float m_run = -INFINITY, l_run = 0.f;

        int slot = 0;
        uint32_t phase = 0;
        auto advance = [&]() {
            if (++slot == kSlots) { slot = 0; phase ^= 1; }
        };
        auto release_and_advance = [&]() {
            mbar_arrive_pred(empty0 + 8 * slot, lane0);
            advance();
        };
        auto do_qk = [&]() -> float {
            const uint32_t d = ring_lo + slot * (kStageBytes >> 4) + (1u << 16);
            mbar_wait(full0 + 8 * slot, phase);
            wg_fence();
            wgmma_n64_first<0>(s, qa + 0, d);
            wgmma_n64_acc<2>(s, qa + 4, d);
            wgmma_n64_acc<4>(s, qa + 8, d);
            wgmma_n64_acc<6>(s, qa + 12, d);
            wgmma_n64_acc<512>(s, qa + 16, d);
            wgmma_n64_acc<514>(s, qa + 20, d);
            wgmma_n64_acc<516>(s, qa + 24, d);
            wgmma_n64_acc<518>(s, qa + 28, d);
            wg_commit();
            wg_wait<0>();
            reg_fence(s);
            release_and_advance();
            const float mx0 = fmaxf(fmaxf(s[0], s[1]), fmaxf(s[4], s[5]));
            const float mx1 = fmaxf(fmaxf(s[8], s[9]), fmaxf(s[12], s[13]));
            const float mx2 = fmaxf(fmaxf(s[16], s[17]), fmaxf(s[20], s[21]));
            const float mx3 = fmaxf(fmaxf(s[24], s[25]), fmaxf(s[28], s[29]));
            float mx = fmaxf(fmaxf(mx0, mx1), fmaxf(fmaxf(mx2, mx3), m_run));
            mx = fmaxf(mx, __shfl_xor_sync(0xffffffffu, mx, 1));
            const float m_new = fmaxf(mx, __shfl_xor_sync(0xffffffffu, mx, 2));
            const float alpha = ex2((m_run - m_new) * kScaleLog2);
            const float mb = m_new * kScaleLog2;
            m_run = m_new;
            float sum0 = 0.f, sum1 = 0.f;
#pragma unroll
            for (int i = 0; i < 8; i++) {
                s[4 * i] = ex2(fmaf(s[4 * i], kScaleLog2, -mb));
                s[4 * i + 1] = ex2(fmaf(s[4 * i + 1], kScaleLog2, -mb));
                sum0 += s[4 * i];
                sum1 += s[4 * i + 1];
            }
            l_run = l_run * alpha + (sum0 + sum1);
            return alpha;
        };
        auto pack_p = [&](uint32_t (&p)[16], float f) {
#pragma unroll
            for (int i = 0; i < 8; i++) {
                p[2 * i] = pack_bf16(s[4 * i] * f, s[4 * i + 1] * f);
                asm volatile("" : "=r"(p[2 * i + 1]));
            }
            reg_fence(p);
        };
        auto rescale = [&](float alpha) {
#pragma unroll
            for (int i = 0; i < 16; i++) {
                asm volatile("mul.f32 %0, %0, %1;" : "+f"(o[4 * i]) : "f"(alpha));
                asm volatile("mul.f32 %0, %0, %1;" : "+f"(o[4 * i + 1]) : "f"(alpha));
            }
        };
        auto issue_pv = [&](uint32_t (&p)[16]) {
            const uint32_t d = ring_lo + slot * (kStageBytes >> 4) + ((8192u >> 4) << 16);
            reg_fence(o);
            reg_fence(p);
            mbar_wait(full0 + 8 * slot, phase);
            wg_fence();
            wgmma_n128_t<0>(o, p + 0, d);
            wgmma_n128_t<128>(o, p + 4, d);
            wgmma_n128_t<256>(o, p + 8, d);
            wgmma_n128_t<384>(o, p + 12, d);
            wg_commit();
        };
        auto issue_pv_next = [&](uint32_t (&p)[16]) {
            const uint32_t d = ring_lo + slot * (kStageBytes >> 4) + ((8192u >> 4) << 16);
            mbar_wait(full0 + 8 * slot, phase);
            wg_fence();
            wgmma_n128_t<0>(o, p + 0, d);
            wgmma_n128_t<128>(o, p + 4, d);
            wgmma_n128_t<256>(o, p + 8, d);
            wgmma_n128_t<384>(o, p + 12, d);
            wg_commit();
        };
        auto do_pv = [&](uint32_t (&p)[16]) {
            issue_pv(p);
            wg_wait<0>();
            reg_fence(o);
            reg_fence(p);
            release_and_advance();
        };

        const uint32_t mlbar = sbase + kMlBarOff + (wg * 4 + w4) * 8;
        const uint32_t mlrow = sbase + kMlOff + wg * 256 + ((toff >> 6) << 3);
        float a1, a2, a3;
#pragma unroll 1
        for (int blk = 0;; blk++) {
            rescale(do_qk());
            pack_p(p0, 1.f);
            a1 = do_qk();
            pack_p(p1, 1.f);
            a2 = do_qk();
            pack_p(p2, 1.f);
            a3 = do_qk();
            if (blk == kTilesWG / 4 - 1) break;
            pack_p(p3, 1.f);
            do_pv(p0);
            rescale(a1);
            do_pv(p1);
            rescale(a2);
            do_pv(p2);
            rescale(a3);
            do_pv(p3);
        }
        {
            float l_tot = l_run + __shfl_xor_sync(0xffffffffu, l_run, 1);
            l_tot += __shfl_xor_sync(0xffffffffu, l_tot, 2);
            asm volatile("bar.sync %0, 128;" ::"r"(5 + wg) : "memory");
            asm volatile("barrier.cluster.wait.acquire.aligned;" ::: "memory");
            if (t == 0)
                asm volatile("st.async.shared::cluster.mbarrier::complete_tx::bytes.v2.f32 [%0], {%1, %2}, [%3];"
                             ::"r"(map_to_cta(mlrow, rank ^ 1)), "f"(m_run), "f"(l_tot), "r"(map_to_cta(mlbar, rank ^ 1)) : "memory");
            mbar_wait_cluster(mlbar, 0);
            float m0, l0;
            asm volatile("ld.shared.v2.f32 {%0, %1}, [%2];" : "=f"(m0), "=f"(l0) : "r"(mlrow) : "memory");
            const float m = fmaxf(m0, m_run);
            const float e0 = ex2((m0 - m) * kScaleLog2), e1 = ex2((m_run - m) * kScaleLog2);
            const float f = __fdividef(e1, l0 * e0 + l_tot * e1);
            const float g2 = a3 * f, g1 = a2 * g2, g0 = a1 * g1;
            auto scale_p = [&](uint32_t (&p)[16], float gf) {
#pragma unroll
                for (int i = 0; i < 8; i++)
                    p[2 * i] = pack_bf16(__uint_as_float(p[2 * i] << 16) * gf, __uint_as_float(p[2 * i] & 0xffff0000u) * gf);
            };
            pack_p(p3, f);
            scale_p(p0, g0);
            scale_p(p1, g1);
            scale_p(p2, g2);
            rescale(g0);
        }
        const uint32_t xbuf = sbase + wg * kRingBytes + kLastKSlot * kStageBytes + toff;
        const uint32_t hand = sbase + kHandOff + w4 * 8;
        const uint32_t xbuf_peer = map_to_cta(xbuf, rank ^ 1), hand_peer = map_to_cta(hand, rank ^ 1);
        const uint32_t tbuf = sbase + wg * kRingBytes + (kLastKSlot - 1) * kStageBytes + w4 * 2176;
        const uint32_t st_addr = __shfl_sync(0xffffffffu, tbuf + (lane & 7) * 272 + (lane >> 3) * 16, lane);
        const uint32_t ld_addr = __shfl_sync(0xffffffffu, tbuf + (lane >> 4) * 272 + (lane & 15) * 16, lane);
        char* op = reinterpret_cast<char*>(out) +
                   __shfl_sync(0xffffffffu, (uint32_t)(((c + 64 * wg) * kRows + w4 * 8) * kD * 2 + lane * 16), lane);
        reg_fence(p1);
        reg_fence(p2);
        reg_fence(p3);
        issue_pv(p0);
        advance();
        issue_pv_next(p1);
        advance();
        issue_pv_next(p2);
        advance();
        issue_pv_next(p3);
        float x[32];
        if (wg != rank) {
            mbar_wait_cluster(hand, 0);
#pragma unroll
            for (int i = 0; i < 8; i++) lds_f32x4(xbuf + i * 2048, x[4 * i], x[4 * i + 1], x[4 * i + 2], x[4 * i + 3]);
        }
        wg_wait<0>();
        reg_fence(o);
        reg_fence(p0);
        reg_fence(p1);
        reg_fence(p2);
        reg_fence(p3);
        if (wg == rank) {
#pragma unroll
            for (int i = 0; i < 8; i++)
                asm volatile("st.async.shared::cluster.mbarrier::complete_tx::bytes.v4.f32 [%0], {%1, %2, %3, %4}, [%5];"
                             ::"r"(xbuf_peer + i * 2048), "f"(o[8 * i]), "f"(o[8 * i + 1]), "f"(o[8 * i + 4]), "f"(o[8 * i + 5]), "r"(hand_peer) : "memory");
        } else {
            uint32_t r[16];
#pragma unroll
            for (int i = 0; i < 8; i++) {
                r[2 * i] = pack_bf16(o[8 * i] + x[4 * i], o[8 * i + 1] + x[4 * i + 1]);
                r[2 * i + 1] = pack_bf16(o[8 * i + 4] + x[4 * i + 2], o[8 * i + 5] + x[4 * i + 3]);
            }
#pragma unroll
            for (int i = 0; i < 4; i++)
                asm volatile("stmatrix.sync.aligned.m8n8.x4.shared.b16 [%0], {%1, %2, %3, %4};"
                             ::"r"(st_addr + 64 * i), "r"(r[4 * i]), "r"(r[4 * i + 1]), "r"(r[4 * i + 2]), "r"(r[4 * i + 3]) : "memory");
            __syncwarp();
#pragma unroll
            for (int i = 0; i < 4; i++) {
                uint4 v;
                asm volatile("ld.shared.v4.b32 {%0, %1, %2, %3}, [%4];"
                             : "=r"(v.x), "=r"(v.y), "=r"(v.z), "=r"(v.w) : "r"(ld_addr + i * 544) : "memory");
                __stcg(reinterpret_cast<uint4*>(op + 512 * i), v);
            }
        }
    }
}

typedef CUresult (*EncodeFn)(CUtensorMap*, CUtensorMapDataType, cuuint32_t, void*, const cuuint64_t*,
                             const cuuint64_t*, const cuuint32_t*, const cuuint32_t*, CUtensorMapInterleave,
                             CUtensorMapSwizzle, CUtensorMapL2promotion, CUtensorMapFloatOOBfill);

void make_kv_map(EncodeFn enc, CUtensorMap* tm, const void* ptr) {
    cuuint64_t dims[3] = {64, (cuuint64_t)kPairs * kSk, 2};
    cuuint64_t strides[2] = {kD * 2, 128};
    cuuint32_t box[3] = {64, (cuuint32_t)kTile, 2};
    cuuint32_t estr[3] = {1, 1, 1};
    enc(tm, CU_TENSOR_MAP_DATA_TYPE_BFLOAT16, 3, const_cast<void*>(ptr), dims, strides, box, estr,
        CU_TENSOR_MAP_INTERLEAVE_NONE, CU_TENSOR_MAP_SWIZZLE_128B, CU_TENSOR_MAP_L2_PROMOTION_L2_256B,
        CU_TENSOR_MAP_FLOAT_OOB_FILL_NONE);
}

}

extern "C" void kernel_launch(void* const* d_in, const int* in_sizes, int n_in, void* d_out, int out_size) {
    (void)in_sizes; (void)n_in; (void)out_size;
    static EncodeFn enc = nullptr;
    if (!enc) {
        cudaDriverEntryPointQueryResult qr;
        void* fn = nullptr;
        cudaGetDriverEntryPoint("cuTensorMapEncodeTiled", &fn, cudaEnableDefault, &qr);
        enc = (EncodeFn)fn;
        cudaFuncSetAttribute(gqa_decode_kernel, cudaFuncAttributeMaxDynamicSharedMemorySize, kSmemBytes);
    }
    CUtensorMap tmK, tmV;
    make_kv_map(enc, &tmK, d_in[1]);
    make_kv_map(enc, &tmV, d_in[2]);
    gqa_decode_kernel<<<kPairs, kThreads, kSmemBytes, cudaStreamPerThread>>>(
        tmK, tmV, (const __nv_bfloat16*)d_in[0], (__nv_bfloat16*)d_out);
}
```
